```python
import torch

def _softmax(x, axis=-1):
    return torch.softmax(x, dim=axis)
def _gelu(x):
    return torch.nn.functional.gelu(x, approximate="tanh")
def _silu(x):
    return torch.nn.functional.silu(x)
def _sigmoid(x):
    return torch.sigmoid(x)
def _layernorm(x, axis=-1, eps=1e-5):
    m = x.mean(dim=axis, keepdim=True)
    v = x.var(dim=axis, keepdim=True, unbiased=False)
    return (x - m) / torch.sqrt(v + eps)
def _scatter_add(tgt, idx, src, axis=0):
    return tgt.clone().index_add_(axis, idx, src)
def _segment_sum(src, seg, n):
    out = torch.zeros((n,) + src.shape[1:], dtype=src.dtype)
    return out.index_add_(0, seg, src)
def _pad(x, pw):
    flat = tuple(v for pair in reversed(pw) for v in pair)
    return torch.nn.functional.pad(x, flat)

kernel_name = 'standalone__edge_featured_mpnn_mpnn__graph'

def setup_inputs():

    _w = (lambda a: (lambda t: t.to(torch.bfloat16) if t.is_floating_point() else t)(torch.as_tensor(a)))
    N, deg, D, De = 10000, 16, 128, max(0, 1)
    E = N * deg
    H = 2 * D
    return {
        "x": _w((lambda *s: torch.randn(*s, dtype=torch.bfloat16) * 0.05)(N, D)),
        "e_attr": _w((lambda *s: torch.randn(*s, dtype=torch.bfloat16) * 1.6)(E, De)),
        "src": _w((lambda lo, hi, *s: torch.randint(lo, hi, s))(0, N, E).to(torch.int64)),
        "dst": _w((lambda lo, hi, *s: torch.randint(lo, hi, s))(0, N, E).to(torch.int64)),
        "w1": _w((lambda *s: torch.randn(*s, dtype=torch.bfloat16) * 1.6)(2 * D + De, H) * (1.0 / (2 * D + De) ** 0.5)),
        "b1": _w((lambda *s: torch.randn(*s, dtype=torch.bfloat16) * 1.6)(H) * 0.01),
        "w2": _w((lambda *s: torch.randn(*s, dtype=torch.bfloat16) * 0.05)(H, D) * (1.0 / H ** 0.5)),
        "b2": _w((lambda *s: torch.randn(*s, dtype=torch.bfloat16) * 0.05)(D) * 0.01),
    }

def reference(x, e_attr, src, dst, w1, b1, w2, b2):
    N, D = x.shape
    h_src = x[src]
    h_dst = x[dst]
    m_in = torch.concatenate([h_src, h_dst, e_attr], axis=-1)
    h = _silu(m_in @ w1 + b1)
    msg = h @ w2 + b2
    return _segment_sum(msg, dst, N)
```

```cpp
#include <cuda_runtime.h>
#include <cuda_bf16.h>
#include <cuda.h>
#include <stdint.h>

namespace {

constexpr int N_NODES = 10000;
constexpr int N_EDGES = 160000;
constexpr int G = 132;
constexpr int NB = 76;
constexpr int EPB = 1216;
constexpr int CELL_CAP = 24;
constexpr int NCHUNK = G * 8;
constexpr int CAP = 1536;
constexpr int DUMMY_ID = 79;
#define EDGE_NS 0
#define CELL_NS 600
#define X_AFTER 4
#define X_NS 0
#define CHAIN 2

constexpr uint32_t HALF2 = 0x3f003f00u;
#define MPNN_NW 24
#define MPNN_U 2
constexpr int NW = MPNN_NW;
constexpr int NT = NW * 32;
constexpr int U = MPNN_U;

constexpr int SM_W0 = 0;
constexpr int SM_W1 = 65536;
constexpr int SM_X = 131072;
constexpr int SM_STAGE = 151552;
constexpr int SM_CONST = SM_STAGE + G * 128;
constexpr int SM_LIST = SM_CONST + 1280;
constexpr int FLEN = CAP + 32;
constexpr int SM_CCNT = SM_LIST + FLEN * 8;
constexpr int SM_NCNT = SM_CCNT + 136 * 4;
constexpr int SM_OCNT = SM_NCNT + 96 * 4;
constexpr int SM_OCUR = SM_OCNT + 96 * 4;
constexpr int SM_OFF = SM_OCUR + 96 * 4;
constexpr int SM_DEG = SM_OFF + 96 * 4;
constexpr int SM_FLAG = SM_DEG + 96 * 4;
constexpr int SM_DUMMY = SM_FLAG + 32 * 4;
constexpr int SM_MISC = SM_DUMMY + 32 * 4;
constexpr int SM_ZEND = SM_MISC + 8 * 4;
constexpr int SM_LAUNCH = SM_ZEND;
constexpr int SM_MBAR = SM_LAUNCH + 8;
constexpr int SM_END = SM_MBAR + 16 * 8;
constexpr int SMEM_BYTES = SM_END + 1024;
static_assert(SM_MBAR % 8 == 0, "align");
static_assert(SM_LIST % 16 == 0 && SM_NCNT % 16 == 0 && SM_CONST % 16 == 0, "align");
static_assert(NW == 24, "NW");
constexpr int WS = NW - 1;
constexpr int LT = WS * 32;
constexpr int ST = (WS - 16) * 32;
constexpr int WTOT = 5 * WS + (WS >> 2);

struct __align__(128) GridBar { unsigned int v; unsigned int pad[31]; };

__device__ __align__(1024) uint4 g_P[G * NB * 32];
__device__ __align__(1024) uint4 g_cells[G * NCHUNK];
__device__ uint2 g_ovf[G * EPB];
__device__ int g_ovfn[G];
__device__ float g_acc[G * NB * 256];
__device__ GridBar g_bar;
#define TS(i) do { } while (0)

__device__ __forceinline__ float tanh_fast(float x) { float y; asm("tanh.approx.f32 %0, %1;" : "=f"(y) : "f"(x)); return y; }
__device__ __forceinline__ uint32_t pack_bf16(float lo, float hi) { uint32_t r; asm("cvt.rn.bf16x2.f32 %0, %1, %2;" : "=r"(r) : "f"(hi), "f"(lo)); return r; }
__device__ __forceinline__ uint32_t hfma2_hi(uint32_t a, uint32_t b, uint32_t c) {
    uint32_t r;
    asm("{.reg .b16 l, h; .reg .b32 t; mov.b32 {l, h}, %1; mov.b32 t, {h, h}; fma.rn.bf16x2 %0, t, %2, %3;}" : "=r"(r) : "r"(a), "r"(b), "r"(c));
    return r;
}
__device__ __forceinline__ uint32_t hadd2(uint32_t a, uint32_t b) { uint32_t r; asm("add.rn.bf16x2 %0, %1, %2;" : "=r"(r) : "r"(a), "r"(b)); return r; }
__device__ __forceinline__ uint32_t hmul2(uint32_t a, uint32_t b) { uint32_t r; asm("mul.rn.bf16x2 %0, %1, %2;" : "=r"(r) : "r"(a), "r"(b)); return r; }
__device__ __forceinline__ float bf_lo(uint32_t v) { return __uint_as_float(v << 16); }
__device__ __forceinline__ float bf_hi(uint32_t v) { return __uint_as_float(v & 0xffff0000u); }
__device__ __forceinline__ uint4 lds128(uint32_t a) { uint4 v; asm volatile("ld.shared.v4.u32 {%0,%1,%2,%3}, [%4];" : "=r"(v.x), "=r"(v.y), "=r"(v.z), "=r"(v.w) : "r"(a) : "memory"); return v; }
__device__ __forceinline__ uint2 lds64(uint32_t a) { uint2 v; asm volatile("ld.shared.v2.u32 {%0,%1}, [%2];" : "=r"(v.x), "=r"(v.y) : "r"(a) : "memory"); return v; }
__device__ __forceinline__ uint32_t lds32(uint32_t a) { uint32_t v; asm volatile("ld.shared.u32 %0, [%1];" : "=r"(v) : "r"(a) : "memory"); return v; }
__device__ __forceinline__ uint32_t lds8(uint32_t a) { uint32_t v; asm volatile("ld.shared.u8 %0, [%1];" : "=r"(v) : "r"(a) : "memory"); return v; }
__device__ __forceinline__ void sts128(uint32_t a, uint32_t x, uint32_t y, uint32_t z, uint32_t w) { asm volatile("st.shared.v4.u32 [%0], {%1,%2,%3,%4};" :: "r"(a), "r"(x), "r"(y), "r"(z), "r"(w) : "memory"); }
__device__ __forceinline__ void sts32(uint32_t a, uint32_t x) { asm volatile("st.shared.u32 [%0], %1;" :: "r"(a), "r"(x) : "memory"); }
__device__ __forceinline__ void sts8(uint32_t a, uint32_t x) { asm volatile("st.shared.u8 [%0], %1;" :: "r"(a), "r"(x) : "memory"); }
__device__ __forceinline__ uint32_t atoms_inc(uint32_t a) { uint32_t r; asm volatile("atom.shared.add.u32 %0, [%1], 1;" : "=r"(r) : "r"(a) : "memory"); return r; }
__device__ __forceinline__ void stg128(void* p, const uint4& v) { asm volatile("st.global.v4.u32 [%0], {%1,%2,%3,%4};" :: "l"(p), "r"(v.x), "r"(v.y), "r"(v.z), "r"(v.w) : "memory"); }
__device__ __forceinline__ uint4 ldg128_l2(const void* p) { uint4 v; asm volatile("ld.relaxed.gpu.global.v4.u32 {%0,%1,%2,%3}, [%4];" : "=r"(v.x), "=r"(v.y), "=r"(v.z), "=r"(v.w) : "l"(p) : "memory"); return v; }
__device__ __forceinline__ void tma_load(uint32_t dst, const CUtensorMap* m, int c0, int c1, uint32_t bar) {
    asm volatile("cp.async.bulk.tensor.2d.shared::cluster.global.mbarrier::complete_tx::bytes [%0], [%1, {%2, %3}], [%4];" :: "r"(dst), "l"(m), "r"(c0), "r"(c1), "r"(bar) : "memory");
}
__device__ __forceinline__ void tma_store(const CUtensorMap* m, int c0, int c1, uint32_t srcaddr) {
    asm volatile("cp.async.bulk.tensor.2d.global.shared::cta.bulk_group [%0, {%1, %2}], [%3];" :: "l"(m), "r"(c0), "r"(c1), "r"(srcaddr) : "memory");
}
__device__ __forceinline__ void bulk_load(uint32_t dst, const void* p, uint32_t bytes, uint32_t bar) {
    asm volatile("cp.async.bulk.shared::cluster.global.mbarrier::complete_tx::bytes [%0], [%1], %2, [%3];" :: "r"(dst), "l"(p), "r"(bytes), "r"(bar) : "memory");
}
__device__ __forceinline__ void prefetch_map(const CUtensorMap* m) { asm volatile("prefetch.tensormap [%0];" :: "l"(m) : "memory"); }
__device__ __forceinline__ bool elect_one() {
    uint32_t p;
    asm volatile("{.reg .pred p; elect.sync _|p, 0xffffffff; selp.u32 %0, 1, 0, p;}" : "=r"(p));
    return p != 0;
}
__device__ __forceinline__ uint32_t lds16(uint32_t a) { uint32_t v; asm volatile("ld.shared.u16 %0, [%1];" : "=r"(v) : "r"(a) : "memory"); return v; }
__device__ __forceinline__ void smem_wait(uint32_t a) {
    asm volatile("{.reg .pred p, q; .reg .u32 n, v; mov.u32 n, 0;\n"
                 "W%=: ld.acquire.cta.shared.u32 v, [%0]; setp.eq.u32 p, v, 0;\n"
                 "add.u32 n, n, 1; setp.lt.u32 q, n, 0x4000000; and.pred q, q, p; @q bra W%=;}" :: "r"(a) : "memory");
}
__device__ __forceinline__ void spin_cycles(uint32_t n) {
    asm volatile("{.reg .pred p; .reg .u32 t0, t; mov.u32 t0, %clock;\n"
                 "S%=: nanosleep.u32 20; mov.u32 t, %clock; sub.u32 t, t, t0; setp.lt.u32 p, t, %0; @p bra S%=;}" :: "r"(n) : "memory");
}
__device__ __forceinline__ void expect_tx(uint32_t bar, uint32_t bytes) { asm volatile("mbarrier.arrive.expect_tx.shared::cta.b64 _, [%0], %1;" :: "r"(bar), "r"(bytes) : "memory"); }
__device__ __forceinline__ bool bar_or(int id, int n, bool p) {
    uint32_t r;
    asm volatile("{.reg .pred p, q; setp.ne.u32 p, %3, 0; bar.red.or.pred q, %1, %2, p; selp.u32 %0, 1, 0, q;}" : "=r"(r) : "r"(id), "r"(n), "r"((uint32_t)p) : "memory");
    return r != 0;
}
__device__ __forceinline__ void mbar_wait(uint32_t bar) {
    asm volatile("{.reg .pred p, q; .reg .u32 n; mov.u32 n, 0;\n"
                 "W%=: mbarrier.try_wait.parity.shared::cta.b64 p, [%0], 0;\n"
                 "add.u32 n, n, 1; setp.lt.u32 q, n, 0x1000000; and.pred q, q, !p; @q bra W%=;}" :: "r"(bar) : "memory");
}
__device__ __forceinline__ void fence_async() { asm volatile("fence.proxy.async.shared::cta;" ::: "memory"); }
__device__ __forceinline__ void bar_sync(int id, int n) { asm volatile("bar.sync %0, %1;" :: "r"(id), "r"(n) : "memory"); }
__device__ __forceinline__ void bar_arrive(int id, int n) { asm volatile("bar.arrive %0, %1;" :: "r"(id), "r"(n) : "memory"); }
__device__ __forceinline__ void stsm4t(uint32_t a, uint32_t r0, uint32_t r1, uint32_t r2, uint32_t r3) {
    asm volatile("stmatrix.sync.aligned.m8n8.x4.trans.shared.b16 [%0], {%1,%2,%3,%4};" :: "r"(a), "r"(r0), "r"(r1), "r"(r2), "r"(r3) : "memory");
}
__device__ __forceinline__ uint32_t desc_lo(uint32_t addr) { return __shfl_sync(0xffffffffu, ((addr & 0x3FFFF) >> 4) | 0x10000u, 0); }
template <int ACC>
__device__ __forceinline__ void wgmma80(float* d, uint32_t la, uint32_t lb) {
    asm volatile("{.reg .pred p; .reg .b64 da, db; setp.ne.b32 p, %42, 0;\n"
        "mov.b64 da, {%40, 0x40000040}; mov.b64 db, {%41, 0x40000040};\n"
        "wgmma.mma_async.sync.aligned.m64n80k16.f32.bf16.bf16 "
        "{%0,%1,%2,%3,%4,%5,%6,%7,%8,%9,%10,%11,%12,%13,%14,%15,%16,%17,%18,%19,"
        "%20,%21,%22,%23,%24,%25,%26,%27,%28,%29,%30,%31,%32,%33,%34,%35,%36,%37,%38,%39}, da, db, p, 1, 1, 1, 0;}\n"
        : "+f"(d[0]), "+f"(d[1]), "+f"(d[2]), "+f"(d[3]), "+f"(d[4]), "+f"(d[5]), "+f"(d[6]), "+f"(d[7]), "+f"(d[8]), "+f"(d[9]),
          "+f"(d[10]), "+f"(d[11]), "+f"(d[12]), "+f"(d[13]), "+f"(d[14]), "+f"(d[15]), "+f"(d[16]), "+f"(d[17]), "+f"(d[18]), "+f"(d[19]),
          "+f"(d[20]), "+f"(d[21]), "+f"(d[22]), "+f"(d[23]), "+f"(d[24]), "+f"(d[25]), "+f"(d[26]), "+f"(d[27]), "+f"(d[28]), "+f"(d[29]),
          "+f"(d[30]), "+f"(d[31]), "+f"(d[32]), "+f"(d[33]), "+f"(d[34]), "+f"(d[35]), "+f"(d[36]), "+f"(d[37]), "+f"(d[38]), "+f"(d[39])
        : "r"(la), "r"(lb), "n"(ACC) : "memory");
}
template <int KS, int BSTRIDE>
__device__ __forceinline__ void gemm80(float* d, uint32_t la, uint32_t lb) {
    asm volatile("wgmma.fence.sync.aligned;" ::: "memory");
    wgmma80<0>(d, la, lb);
#pragma unroll
    for (int s = 1; s < KS; s++) wgmma80<1>(d, la + s * 128, lb + (s >> 2) * (BSTRIDE / 16) + (s & 3) * 2);
    asm volatile("wgmma.commit_group.sync.aligned;" ::: "memory");
}
__device__ __forceinline__ void wg_wait(float* d) {
    asm volatile("wgmma.wait_group.sync.aligned 0;" ::: "memory");
#pragma unroll
    for (int i = 0; i < 40; i++) asm volatile("" : "+f"(d[i]) :: "memory");
}
__device__ __forceinline__ void grid_arrive(GridBar* b) {
    asm volatile("red.relaxed.gpu.global.add.u32 [%0], %1;" :: "l"(&b->v), "r"(blockIdx.x == 0 ? 256u - (G - 1) : 1u) : "memory");
}
__device__ __forceinline__ uint32_t grid_peek(GridBar* b) {
    uint32_t v;
    asm volatile("ld.relaxed.gpu.global.u32 %0, [%1];" : "=r"(v) : "l"(&b->v) : "memory");
    return v;
}
__device__ __forceinline__ void grid_wait(GridBar* b, uint32_t peek) {
    asm volatile("{.reg .pred p, q; .reg .u32 n, v; mov.u32 n, 0;\n"
                 "W%=: ld.acquire.gpu.global.u32 v, [%0]; xor.b32 v, v, %1; setp.lt.u32 p, v, 256;\n"
                 "add.u32 n, n, 1; setp.lt.u32 q, n, 0x400000; and.pred q, q, p; @q bra W%=;}" :: "l"(&b->v), "r"(peek) : "memory");
}

constexpr int BAR_READY = 1, BAR_INIT = 2, BAR_LIST = 3, BAR_WG0 = 4, BAR_P0 = 8, BAR_CHAIN0 = 12;
constexpr int MB_X = 8, MB_C = 9, MB_W2 = 10;

template <class F>
__device__ __forceinline__ void for_overflow(uint32_t sb, int node0, int first, int stride, F f) {
#pragma unroll 1
    for (int m = 0; m < 5; m++) {
        uint32_t bits = lds32(sb + SM_MISC + m * 4);
#pragma unroll 1
        while (bits) {
            const int s = m * 32 + __ffs(bits) - 1;
            bits &= bits - 1;
            const int n = __ldcg(&g_ovfn[s]);
#pragma unroll 1
            for (int i = first; i < n; i += stride) {
                const uint2 en = __ldcg(&g_ovf[s * EPB + i]);
                const uint32_t id = en.x - (uint32_t)node0;
                if (id < (uint32_t)NB) f(id, en.y);
            }
        }
    }
}

__device__ __forceinline__ void put_entry(uint32_t base, uint32_t pos, uint32_t id, uint32_t word, bool ok) {
    asm volatile("{.reg .pred p; setp.ne.u32 p, %3, 0; @p st.shared.v2.u32 [%0], {%1, %2};}"
                 :: "r"(base + pos * 8), "r"(word & 0xffffu), "r"((word & 0xffff0000u) | id), "r"((uint32_t)ok) : "memory");
}
__device__ __noinline__ void cold_spill(uint32_t sb, uint32_t dv, uint32_t word) {
    const uint32_t o = atoms_inc(sb + SM_MISC + 5 * 4);
    g_ovf[blockIdx.x * EPB + o] = make_uint2(dv, word);
    sts8(sb + SM_STAGE + (dv / NB) * 128 + 15, 0u);
}
__device__ __noinline__ void cold_spill_publish(uint32_t sb) {
    if (threadIdx.x == 0) g_ovfn[blockIdx.x] = (int)lds32(sb + SM_MISC + 5 * 4);
    __threadfence();
    bar_sync(BAR_READY, LT);
}
__device__ __noinline__ void cold_mark(uint32_t sb, int s) {
    asm volatile("red.shared.or.b32 [%0], %1;" :: "r"(sb + SM_MISC + (s >> 5) * 4), "r"(1u << (s & 31)) : "memory");
}
__device__ __noinline__ void cold_count(uint32_t sb, int lt) {
    __threadfence();
    for_overflow(sb, blockIdx.x * NB, lt, ST, [&](uint32_t id, uint32_t) { atoms_inc(sb + SM_OCNT + id * 4); });
    bar_sync(BAR_LIST, ST);
}
__device__ __noinline__ void cold_put(uint32_t sb, int lt) {
    for_overflow(sb, blockIdx.x * NB, lt, ST, [&](uint32_t id, uint32_t word) {
        put_entry(sb + SM_LIST, lds32(sb + SM_OFF + id * 4) + lds32(sb + SM_NCNT + id * 4) + atoms_inc(sb + SM_OCUR + id * 4), id, word, true);
    });
}
__device__ __noinline__ void cold_direct(uint32_t sb, const uint4* cells, const char* P) {
    const int tid = threadIdx.x, lane = tid & 31, w = tid >> 5, node0 = blockIdx.x * NB;
    auto row_addr = [&](uint32_t id) { return sb + SM_W1 + (lane >> 3) * 16384 + id * 128 + (((lane ^ id) & 7) << 4); };
    const uint4 wc = lds128(sb + SM_CONST + lane * 16);
    smem_wait(sb + SM_MISC + 7 * 4);
    float* accg = g_acc + (size_t)node0 * 256;
#pragma unroll 1
    for (int i = tid; i < NB * 256; i += NT - 32) accg[i] = 0.f;
    bar_sync(BAR_READY, NT - 32);
    auto one = [&](uint32_t id, uint32_t word) {
        const uint4 p = ldg128_l2(P + lane * 16 + (size_t)(word & 0xffffu) * 512), q = lds128(row_addr(id));
        const uint32_t z[4] = {hadd2(hfma2_hi(word, hmul2(wc.x, HALF2), q.x), p.x), hadd2(hfma2_hi(word, hmul2(wc.y, HALF2), q.y), p.y),
                               hadd2(hfma2_hi(word, hmul2(wc.z, HALF2), q.z), p.z), hadd2(hfma2_hi(word, hmul2(wc.w, HALF2), q.w), p.w)};
#pragma unroll
        for (int j = 0; j < 4; j++) {
            const float a = bf_lo(z[j]), b = bf_hi(z[j]);
            atomicAdd(accg + id * 256 + lane * 8 + 2 * j, fmaf(a, tanh_fast(a), a));
            atomicAdd(accg + id * 256 + lane * 8 + 2 * j + 1, fmaf(b, tanh_fast(b), b));
        }
    };
#pragma unroll 1
    for (int c = w * 3; c < NCHUNK * 3; c += (c % 3 == 2) ? WS * 3 - 2 : 1) {
        const uint32_t* cell = (const uint32_t*)(cells + blockIdx.x * NCHUNK + c / 3);
        const uint32_t id = (__ldcg(cell + 3) >> (8 * (c % 3))) & 0xffu;
        if (id != 0xffu) one(id, __ldcg(cell + c % 3));
    }
    for_overflow(sb, node0, w, WS, one);
    __threadfence();
    bar_sync(BAR_READY, NT - 32);
#pragma unroll 1
    for (int n = w; n < NB; n += WS) {
        float a[8];
#pragma unroll
        for (int j = 0; j < 8; j++) a[j] = __ldcg(accg + n * 256 + lane * 8 + j);
        sts128(row_addr(n), pack_bf16(a[0], a[1]), pack_bf16(a[2], a[3]), pack_bf16(a[4], a[5]), pack_bf16(a[6], a[7]));
    }
}

template <int PHASE>
__global__ void __launch_bounds__(NT, 1)
mpnn_kernel(const int2* __restrict__ dst, const int2* __restrict__ src, const uint32_t* __restrict__ ea,
            uint4* cells, const char* P, GridBar* bar, const char* __restrict__ w1, const char* __restrict__ b1, const char* __restrict__ b2,
            const __grid_constant__ CUtensorMap tm_x, const __grid_constant__ CUtensorMap tm_w1, const __grid_constant__ CUtensorMap tm_p,
            const __grid_constant__ CUtensorMap tm_w2, const __grid_constant__ CUtensorMap tm_out) {
    extern __shared__ char smem_raw[];
    const uint32_t sb = ((uint32_t)__cvta_generic_to_shared(smem_raw) + 1023u) & ~1023u;
    const uint32_t mb = sb + SM_MBAR;
    const int tid = threadIdx.x, lane = tid & 31;
    const int w = __shfl_sync(0xffffffffu, tid >> 5, 0);
    const int cta = blockIdx.x;
    const int node0 = cta * NB;
    if (w == 0) TS(0);

    const int wg = w >> 2, wq = w & 3;
    const uint32_t frag_off = (uint32_t)(((lane & 7) + 8 * (lane >> 4)) * 128 + (((2 * wq + ((lane >> 3) & 1)) ^ (lane & 7)) << 4));
    float d[40];
    if (w == WS) {
        const bool el = elect_one();
        if (el) {
            prefetch_map(&tm_x); prefetch_map(&tm_w1);
#pragma unroll
            for (int i = 0; i < 11; i++) asm volatile("mbarrier.init.shared::cta.b64 [%0], 1;" :: "r"(mb + i * 8) : "memory");
            asm volatile("fence.mbarrier_init.release.cluster;" ::: "memory");
        }
        __syncwarp();
        bar_arrive(BAR_INIT, NT);
        if (el) {
#pragma unroll 1
            for (int j = (PHASE == 2 ? 4 : 0); j < (PHASE == 1 ? 4 : 8); j++) {
                if (j == (PHASE == 2 ? 4 : X_AFTER)) {
                    if (X_NS) { const long long t0 = clock64(); while (clock64() - t0 < X_NS * 2) { } }
                    expect_tx(mb + MB_X * 8, 20480);
                    tma_load(sb + SM_X, &tm_x, 0, node0, mb + MB_X * 8);
                    tma_load(sb + SM_X + 10240, &tm_x, 64, node0, mb + MB_X * 8);
                }
                                expect_tx(mb + j * 8, 16384);
                tma_load(sb + SM_W0 + j * 16384, &tm_w1, (j & 3) * 64, (j >> 2) * 128, mb + j * 8);
            }
            expect_tx(mb + MB_C * 8, 1280);
            bulk_load(sb + SM_CONST, w1 + 256 * 512, 512, mb + MB_C * 8);
            bulk_load(sb + SM_CONST + 512, b1, 512, mb + MB_C * 8);
            bulk_load(sb + SM_CONST + 1024, b2, 256, mb + MB_C * 8);
            prefetch_map(&tm_p); prefetch_map(&tm_w2); prefetch_map(&tm_out);
        }
        __syncwarp();
        TS(23);
        if (PHASE != 2) {
#pragma unroll 1
            for (int j = 0; j < 4; j++) {
                bar_sync(BAR_P0 + j, 160);
                if (el) tma_store(&tm_p, j * 64, node0, sb + SM_W0 + j * 16384);
            }
        }
        if (el) {
            if (PHASE != 2) {
                asm volatile("cp.async.bulk.commit_group;" ::: "memory");
                asm volatile("cp.async.bulk.wait_group.read 0;" ::: "memory");
            }
            if (PHASE != 1) {
                expect_tx(mb + MB_W2 * 8, 65536);
                tma_load(sb + SM_W0, &tm_w2, 0, 0, mb + MB_W2 * 8);
                tma_load(sb + SM_W0 + 32768, &tm_w2, 64, 0, mb + MB_W2 * 8);
            }
            if (PHASE != 2) {
                asm volatile("cp.async.bulk.wait_group 0;" ::: "memory");
                asm volatile("fence.acq_rel.gpu;" ::: "memory");
                grid_arrive(bar);
            }
            if (PHASE == 0) grid_wait(bar, lds32(sb + SM_LAUNCH) << 8);
            asm volatile("st.release.cta.shared.u32 [%0], 1;" :: "r"(sb + SM_MISC + 7 * 4) : "memory");
        }
        __syncwarp();
        TS(15);
    } else {
    constexpr int TWO = NCHUNK - LT;
    static_assert(TWO > 0 && TWO <= LT && TWO % 32 == 0, "chunks");
    uint32_t peek = 0;
    if (tid == 0) peek = grid_peek(bar);
    sts32(sb + SM_STAGE + tid * 16 + 12, 0x80ffffffu);
    if (tid < TWO) sts32(sb + SM_STAGE + (LT + tid) * 16 + 12, 0x80ffffffu);
    if (tid < (SM_ZEND - SM_CCNT) / 4) sts32(sb + SM_CCNT + tid * 4, 0u);
    static_assert((SM_ZEND - SM_CCNT) / 4 <= LT && LT - 128 == EPB / 2, "zeroing");
    if (EDGE_NS) __nanosleep(EDGE_NS);
    int2 e_dst = make_int2(-1, -1), e_src = make_int2(0, 0);
    uint32_t e_att = 0;
    if (PHASE != 2) {
        const int e2 = cta * (EPB / 2) + tid - 128;
        if (w >= 4 && e2 < N_EDGES / 2) { e_dst = __ldg(dst + e2); e_src = __ldg(src + e2); e_att = __ldg(ea + e2); }
    }
    bar_sync(BAR_INIT, NT);
    if (tid == 0) sts32(sb + SM_LAUNCH, (PHASE == 2 ? peek - 256u : peek) >> 8);
    if (w == 0) TS(25);
    const uint32_t slab = sb + SM_W0 + wg * 16384;
    const uint32_t la = desc_lo(slab), lb = desc_lo(sb + SM_X);
    bool spilled = false;
    if (PHASE != 2) {
        if (e_dst.x >= 0) {
            const uint32_t dv[2] = {(uint32_t)e_dst.x, (uint32_t)e_dst.y};
            const uint32_t wd[2] = {__byte_perm((uint32_t)e_src.x, e_att, 0x5410), __byte_perm((uint32_t)e_src.y, e_att, 0x7610)};
            uint32_t oc[2], r[2];
#pragma unroll
            for (int k = 0; k < 2; k++) { oc[k] = dv[k] / NB; r[k] = atoms_inc(sb + SM_CCNT + oc[k] * 4); }
#pragma unroll
            for (int k = 0; k < 2; k++) {
                const uint32_t ch = (r[k] * 11) >> 5, p = r[k] - ch * 3;
                const uint32_t a = sb + SM_STAGE + oc[k] * 128 + ch * 16;
                asm volatile("{.reg .pred p; setp.lt.u32 p, %4, 24; @p st.shared.u32 [%0], %1; @p st.shared.u8 [%2], %3;}"
                             :: "r"(a + p * 4), "r"(wd[k]), "r"(a + 12 + p), "r"(dv[k] - oc[k] * NB), "r"(r[k]) : "memory");
            }
            if (__builtin_expect(max(r[0], r[1]) >= CELL_CAP, 0)) {
                if (r[0] >= CELL_CAP) cold_spill(sb, dv[0], wd[0]);
                if (r[1] >= CELL_CAP) cold_spill(sb, dv[1], wd[1]);
                spilled = true;
            }
        }
    }
    if (w == 16) TS(1);
    if (__builtin_expect(bar_or(BAR_READY, LT, spilled), 0)) cold_spill_publish(sb);
    if (w == 16) TS(2);
    const uint32_t launch = lds32(sb + SM_LAUNCH);
    const uint32_t ctag = (launch & 63u) + 1u;
    const uint32_t ptag = (launch + 1u) & 1u;
    if (PHASE != 2) {
        uint4* cp = cells + ((tid >> 3) * G + cta) * 8 + (tid & 7);
        uint4 v = lds128(sb + SM_STAGE + tid * 16);
        v.w |= ctag << 24;
        stg128(cp, v);
        if (tid < TWO) {
            v = lds128(sb + SM_STAGE + (LT + tid) * 16);
            v.w |= ctag << 24;
            stg128(cp + (LT / 8) * G * 8, v);
        }
        if (w == 16) TS(28);
        if (w < 16) {
            mbar_wait(mb + MB_X * 8);
            if (w == 0) TS(3);
            mbar_wait(mb + wg * 8);
            if (w == 0) TS(4);
            if (CHAIN && wg > 0) bar_sync(BAR_CHAIN0 + wg - 1, 256);
            gemm80<8, 10240>(d, la, lb);
            if (CHAIN == 1 && wg < 3) bar_arrive(BAR_CHAIN0 + wg, 256);
            const uint32_t keep = (lane < 4) ? 0xfffefffeu : 0xffffffffu, set = (lane < 4) ? ptag * 0x00010001u : 0u;
            wg_wait(d);
            if (CHAIN == 2 && wg < 3) bar_arrive(BAR_CHAIN0 + wg, 256);
            if (w == 0) TS(29);
            bar_sync(BAR_WG0 + wg, 128);
#pragma unroll
            for (int i = 0; i < 5; i++)
                stsm4t(slab + i * 2048 + frag_off,
                       (hmul2(pack_bf16(d[8 * i + 0], d[8 * i + 1]), HALF2) & keep) | set, (hmul2(pack_bf16(d[8 * i + 2], d[8 * i + 3]), HALF2) & keep) | set,
                       (hmul2(pack_bf16(d[8 * i + 4], d[8 * i + 5]), HALF2) & keep) | set, (hmul2(pack_bf16(d[8 * i + 6], d[8 * i + 7]), HALF2) & keep) | set);
            fence_async();
            bar_arrive(BAR_P0 + wg, 160);
            if (wq == 0) TS(5 + wg);
        }
    }
    if (PHASE != 1) {
    if (w < 16) {
        if (PHASE == 2) mbar_wait(mb + MB_X * 8);
        mbar_wait(mb + (4 + wg) * 8);
        if (w == 0) TS(30);
        gemm80<8, 10240>(d, la + 4096, lb);
        mbar_wait(mb + MB_C * 8);
        const uint32_t ba = sb + SM_CONST + 512 + (w * 16 + (lane >> 2)) * 2;
        const float bl = 0.5f * bf_lo(lds16(ba)), bh = 0.5f * bf_lo(lds16(ba + 16));
        wg_wait(d);
        bar_sync(BAR_WG0 + wg, 128);
#pragma unroll
        for (int i = 0; i < 5; i++)
            stsm4t(slab + 65536 + i * 2048 + frag_off,
                   pack_bf16(fmaf(d[8 * i + 0], 0.5f, bl), fmaf(d[8 * i + 1], 0.5f, bl)), pack_bf16(fmaf(d[8 * i + 2], 0.5f, bh), fmaf(d[8 * i + 3], 0.5f, bh)),
                   pack_bf16(fmaf(d[8 * i + 4], 0.5f, bl), fmaf(d[8 * i + 5], 0.5f, bl)), pack_bf16(fmaf(d[8 * i + 6], 0.5f, bh), fmaf(d[8 * i + 7], 0.5f, bh)));
        if (w == 0) TS(9);
    } else {
        const int st = tid - 512;
        constexpr int CPT = (NCHUNK + ST - 1) / ST, LASTW = 16 + (NCHUNK - (CPT - 1) * ST) / 32;
        static_assert((NCHUNK - (CPT - 1) * ST) % 32 == 0, "chunks");
        uint4 cv[CPT]; uint32_t rk[CPT][3];
        const uint4* cp = cells + cta * NCHUNK + st;
#pragma unroll
        for (int k = 0; k < CPT; k++) cv[k].w = (k < CPT - 1 || w < LASTW) ? 0u : (0x80ffffffu | (ctag << 24));
        if (PHASE == 0) spin_cycles(CELL_NS * 2);
        if (w == 16) TS(17);
#pragma unroll 1
        for (int it = 0;; it++) {
            bool stale = false;
#pragma unroll
            for (int k = 0; k < CPT; k++)
                if (((cv[k].w >> 24) & 0x7fu) != ctag) cv[k] = ldg128_l2(cp + k * ST);
#pragma unroll
            for (int k = 0; k < CPT; k++) stale |= ((cv[k].w >> 24) & 0x7fu) != ctag;
            if (!__any_sync(0xffffffffu, stale && it < (1 << 22))) break;
        }
        if (w == 16) TS(26);
        uint32_t allw = 0xffffffffu;
#pragma unroll
        for (int k = 0; k < CPT; k++) {
            rk[k][0] = rk[k][1] = rk[k][2] = 0;
            if (k < CPT - 1 || w < LASTW) {
#pragma unroll
                for (int p = 0; p < 3; p++) {
                    const uint32_t id = (cv[k].w >> (8 * p)) & 0xffu;
                    rk[k][p] = atoms_inc(id != 0xffu ? sb + SM_NCNT + id * 4 : sb + SM_DUMMY + lane * 4);
                }
            }
            allw &= cv[k].w;
        }
        if (__builtin_expect((int)allw >= 0, 0)) {
#pragma unroll
            for (int k = 0; k < CPT; k++)
                if ((int)cv[k].w >= 0) cold_mark(sb, (st + k * ST) >> 3);
        }
        const bool rare = bar_or(BAR_LIST, ST, (int)allw >= 0);
        if (w == 16) TS(27);
        if (__builtin_expect(rare, 0)) cold_count(sb, st);
        {
            const uint32_t a = sb + SM_NCNT + min(lane, 23) * 16;
            uint4 cnt = lds128(a);
            const uint4 o = lds128(a + (SM_OCNT - SM_NCNT));
            cnt.x += o.x; cnt.y += o.y; cnt.z += o.z; cnt.w += o.w;
            const uint32_t s = cnt.x + cnt.y + cnt.z + cnt.w;
            uint32_t inc = s;
#pragma unroll
            for (int o2 = 1; o2 < 32; o2 <<= 1) { const uint32_t t = __shfl_up_sync(0xffffffffu, inc, o2); if (lane >= o2) inc += t; }
            const uint32_t ex = inc - s;
            if (lane < 24) {
                sts128(a + (SM_OFF - SM_NCNT), ex, ex + cnt.x, ex + cnt.x + cnt.y, ex + cnt.x + cnt.y + cnt.z);
                if (w == WS - 1) sts128(a + (SM_DEG - SM_NCNT), __float_as_uint((float)cnt.x), __float_as_uint((float)cnt.y), __float_as_uint((float)cnt.z), __float_as_uint((float)cnt.w));
            }
            const uint32_t tot = __shfl_sync(0xffffffffu, inc, 23);
            __syncwarp();
            if (tot <= (uint32_t)CAP) {
                if (w == 16) TS(13);
#pragma unroll
                for (int k = 0; k < CPT; k++) {
                    if (k < CPT - 1 || w < LASTW) {
                        const uint32_t wd[3] = {cv[k].x, cv[k].y, cv[k].z};
#pragma unroll
                        for (int p = 0; p < 3; p++) {
                            const uint32_t id = (cv[k].w >> (8 * p)) & 0xffu;
                            put_entry(sb + SM_LIST, lds32(sb + SM_OFF + (id & 127u) * 4) + rk[k][p], id, wd[p], id != 0xffu);
                        }
                    }
                }
                if (w == WS - 1) put_entry(sb + SM_LIST, tot + lane, DUMMY_ID, 0u, true);
                if (__builtin_expect(rare, 0)) cold_put(sb, st);
            }
        }
        mbar_wait(mb + MB_C * 8);
        if (w == 16) TS(21);
    }
    const uint32_t lane16 = lane * 16;
    uint32_t sH = sb + SM_W1 + (lane >> 3) * 16384;
    uint32_t lsw = lane16 & 0x70;
    auto row_addr = [&](uint32_t id) { return sH + id * 128 + (lsw ^ ((id << 4) & 0x70)); };
    const char* Pl = P + lane16;
    asm volatile("" : "+l"(Pl), "+r"(sH), "+r"(lsw));
    const uint4 wc_raw = lds128(sb + SM_CONST + lane16);
    const uint32_t wp[4] = {hmul2(wc_raw.x, HALF2), hmul2(wc_raw.y, HALF2), hmul2(wc_raw.z, HALF2), hmul2(wc_raw.w, HALF2)};
    bar_sync(BAR_READY, LT);
    const int T = (int)__shfl_sync(0xffffffffu, lds32(sb + SM_OFF + 95 * 4), 0);
    if (w == 0) TS(14);
    const int nbatch = (T + U - 1) / U;
    auto first_batch = [&](int ww) { return ((5 * ww + (ww >> 2)) * nbatch) / WTOT; };
    const int b0 = first_batch(w), b1 = first_batch(w + 1);

    auto part_addr = [&](int ww) { return sb + SM_W1 + (ww / 6) * 16384 + 10240 + (ww % 6) * 1024 + lane16; };
    auto store_h = [&](uint32_t id, const float* a) {
        sts128(row_addr(id), pack_bf16(a[0], a[1]), pack_bf16(a[2], a[3]), pack_bf16(a[4], a[5]), pack_bf16(a[6], a[7]));
    };
    auto zero_rows = [&]() {
        uint32_t z = __ballot_sync(0xffffffffu, lane < 4 && w + lane * WS < NB && lds32(sb + SM_DEG + (w + (lane & 3) * WS) * 4) == 0u);
#pragma unroll 1
        while (z) { sts128(row_addr(w + (__ffs(z) - 1) * WS), 0u, 0u, 0u, 0u); z &= z - 1; }
    };
    if (__builtin_expect(T <= CAP, 1)) {
        const int e0 = b0 * U, e1 = b1 * U;
        const uint32_t sL = sb + SM_LIST;
        uint32_t cur = 0, mask = 0;
        bool lead = false, chk = true;
        uint32_t qp[4], v[4], yA[U], yB[U];
        uint4 bufA[U], bufB[U];
        float acc[8];
        uint32_t xa = sL + e0 * 8;
        auto load_q = [&](uint32_t id) { const uint4 t = lds128(row_addr(id)); qp[0] = t.x; qp[1] = t.y; qp[2] = t.z; qp[3] = t.w; };
        auto issue = [&](uint32_t a, uint4* buf, uint32_t* y) {
#pragma unroll
            for (int k = 0; k < U; k += 2) {
                const uint4 t = lds128(a + k * 8);
                buf[k] = ldg128_l2(Pl + (size_t)t.x * 512);
                buf[k + 1] = ldg128_l2(Pl + (size_t)t.z * 512);
                y[k] = t.y; y[k + 1] = t.w;
            }
        };
        auto verify = [&](uint32_t a, uint4* buf, uint32_t* y) {
#pragma unroll 1
            for (int it = 0;; it++) {
                uint32_t bad = 0;
#pragma unroll
                for (int k = 0; k < U; k++) bad |= buf[k].x ^ ptag;
                if (!__any_sync(0xffffffffu, (bad & 1u) && it < (1 << 22))) break;
                issue(a, buf, y);
            }
            uint32_t f;
            asm volatile("ld.acquire.cta.shared.u32 %0, [%1];" : "=r"(f) : "r"(sb + SM_MISC + 7 * 4) : "memory");
            chk = __any_sync(0xffffffffu, f == 0u);
        };
        auto refill = [&](int eb) {
            const int i = eb + lane;
            mask = __ballot_sync(0xffffffffu, (i + 1 < e1) && (lds8(sL + i * 8 + 4) != lds8(sL + i * 8 + 12)));
        };
        auto zpart = [&](uint32_t y, const uint4& p, uint32_t* o) {
            o[0] = hadd2(hfma2_hi(y, wp[0], qp[0]), p.x); o[1] = hadd2(hfma2_hi(y, wp[1], qp[1]), p.y);
            o[2] = hadd2(hfma2_hi(y, wp[2], qp[2]), p.z); o[3] = hadd2(hfma2_hi(y, wp[3], qp[3]), p.w);
        };
        auto act = [&]() {
#pragma unroll
            for (int j = 0; j < 4; j++) {
                const float a = bf_lo(v[j]), b = bf_hi(v[j]);
                acc[2 * j] += fmaf(a, tanh_fast(a), a);
                acc[2 * j + 1] += fmaf(b, tanh_fast(b), b);
            }
        };
        auto publish = [&]() {
            const uint32_t pa = part_addr(w);
            sts128(pa, __float_as_uint(acc[0]), __float_as_uint(acc[1]), __float_as_uint(acc[2]), __float_as_uint(acc[3]));
            sts128(pa + 512, __float_as_uint(acc[4]), __float_as_uint(acc[5]), __float_as_uint(acc[6]), __float_as_uint(acc[7]));
            __syncwarp();
            if (lane == 0) asm volatile("st.release.cta.shared.u32 [%0], 1;" :: "r"(sb + SM_FLAG + w * 4) : "memory");
        };
        auto slot = [&](int k, uint32_t yn, const uint4& pn) {
            uint32_t vn[4];
            if (mask & (1u << k)) {
                const uint32_t nid = yn & 0xffu;
                load_q(nid);
                act();
                if (lead) { publish(); lead = false; } else store_h(cur, acc);
#pragma unroll
                for (int j = 0; j < 8; j++) acc[j] = 0.f;
                cur = nid;
                zpart(yn, pn, vn);
            } else {
                zpart(yn, pn, vn);
                act();
            }
#pragma unroll
            for (int j = 0; j < 4; j++) v[j] = vn[j];
        };
        if (b0 < b1) {
            issue(xa, bufA, yA);
            zero_rows();
            cur = yA[0] & 0xffu;
            lead = __any_sync(0xffffffffu, (e0 > 0) && (lds8(xa - 4) == cur));
            load_q(cur);
            refill(e0);
#pragma unroll
            for (int j = 0; j < 8; j++) acc[j] = 0.f;
            verify(xa, bufA, yA);
            issue(xa + U * 8, bufB, yB);
            zpart(yA[0], bufA[0], v);
            if (w == 0) TS(16);
            int e = e0;
            while (true) {
#pragma unroll
                for (int k = 0; k < U - 1; k++) slot(k, yA[k + 1], bufA[k + 1]);
                if (chk) verify(xa + U * 8, bufB, yB);
                slot(U - 1, yB[0], bufB[0]);
                e += U;
                if (e >= e1) break;
                issue(xa + 2 * U * 8, bufA, yA);
#pragma unroll
                for (int k = 0; k < U - 1; k++) slot(U + k, yB[k + 1], bufB[k + 1]);
                if (chk) verify(xa + 2 * U * 8, bufA, yA);
                slot(2 * U - 1, yA[0], bufA[0]);
                mask >>= 2 * U; e += U; xa += 2 * U * 8;
                if (e >= e1) break;
                issue(xa + U * 8, bufB, yB);
                if (((e - e0) & 31) == 0) refill(e);
            }
            if (e1 < T && lds8(sL + e1 * 8 + 4) == cur) {
                int wn = w + 1;
#pragma unroll 1
                while (first_batch(wn + 1) == b1) wn++;
                smem_wait(sb + SM_FLAG + wn * 4);
                const uint4 a = lds128(part_addr(wn)), b = lds128(part_addr(wn) + 512);
                acc[0] += __uint_as_float(a.x); acc[1] += __uint_as_float(a.y); acc[2] += __uint_as_float(a.z); acc[3] += __uint_as_float(a.w);
                acc[4] += __uint_as_float(b.x); acc[5] += __uint_as_float(b.y); acc[6] += __uint_as_float(b.z); acc[7] += __uint_as_float(b.w);
            }
            if (lead) publish(); else store_h(cur, acc);
        } else zero_rows();
    } else cold_direct(sb, cells, P);
    fence_async();
    }
    }
    if (PHASE == 1) return;
    __syncthreads();
    if (w == 0) TS(18);

    if (w < 8) {
        mbar_wait(mb + MB_W2 * 8);
        if (w == 0) TS(10);
        gemm80<16, 16384>(d, desc_lo(sb + SM_W0 + wg * 32768), desc_lo(sb + SM_W1));
        if (w == 0) TS(11);
        const uint32_t ba = sb + SM_CONST + 1024 + (w * 16 + (lane >> 2)) * 2;
        const float c_lo = bf_lo(lds16(ba)), c_hi = bf_lo(lds16(ba + 16));
        wg_wait(d);
        if (w == 0) TS(31);
        const uint32_t stg = sb + SM_X + wg * 10240;
#pragma unroll
        for (int i = 0; i < 5; i++) {
            const uint2 g0 = lds64(sb + SM_DEG + (16 * i + 2 * (lane & 3)) * 4), g1 = lds64(sb + SM_DEG + (16 * i + 8 + 2 * (lane & 3)) * 4);
            const float dg[4] = {__uint_as_float(g0.x), __uint_as_float(g0.y), __uint_as_float(g1.x), __uint_as_float(g1.y)};
            stsm4t(stg + i * 2048 + frag_off,
                   pack_bf16(fmaf(dg[0], c_lo, d[8 * i + 0]), fmaf(dg[1], c_lo, d[8 * i + 1])), pack_bf16(fmaf(dg[0], c_hi, d[8 * i + 2]), fmaf(dg[1], c_hi, d[8 * i + 3])),
                   pack_bf16(fmaf(dg[2], c_lo, d[8 * i + 4]), fmaf(dg[3], c_lo, d[8 * i + 5])), pack_bf16(fmaf(dg[2], c_hi, d[8 * i + 6]), fmaf(dg[3], c_hi, d[8 * i + 7])));
        }
        if (w == 0) TS(12);
        fence_async();
        bar_sync(BAR_WG0 + wg, 128);
        if (wq == 0 && elect_one()) {
            tma_store(&tm_out, wg * 64, node0, stg);
            asm volatile("cp.async.bulk.commit_group;" ::: "memory");
            asm volatile("cp.async.bulk.wait_group.read 0;" ::: "memory");
        }
        if (w == 0) TS(19);
    }
}

}

typedef CUresult (*EncodeTiledFn)(CUtensorMap*, CUtensorMapDataType, cuuint32_t, void*, const cuuint64_t*, const cuuint64_t*,
                                  const cuuint32_t*, const cuuint32_t*, CUtensorMapInterleave, CUtensorMapSwizzle,
                                  CUtensorMapL2promotion, CUtensorMapFloatOOBfill);

static void make_map(EncodeTiledFn enc, CUtensorMap* m, const void* base, int cols, int rows, int box_rows) {
    cuuint64_t dims[2] = {(cuuint64_t)cols, (cuuint64_t)rows};
    cuuint64_t strides[1] = {(cuuint64_t)cols * 2};
    cuuint32_t box[2] = {64, (cuuint32_t)box_rows};
    cuuint32_t estr[2] = {1, 1};
    enc(m, CU_TENSOR_MAP_DATA_TYPE_BFLOAT16, 2, const_cast<void*>(base), dims, strides, box, estr, CU_TENSOR_MAP_INTERLEAVE_NONE,
        CU_TENSOR_MAP_SWIZZLE_128B, CU_TENSOR_MAP_L2_PROMOTION_L2_128B, CU_TENSOR_MAP_FLOAT_OOB_FILL_NONE);
}

extern "C" void kernel_launch(void* const* d_in, const int* in_sizes, int n_in, void* d_out, int out_size) {
    (void)in_sizes; (void)n_in; (void)out_size;
    static int fused = -1;
    static EncodeTiledFn enc = nullptr;
    static void *p_addr = nullptr, *c_addr = nullptr, *bar_addr = nullptr;
    if (fused < 0) {
        cudaFuncSetAttribute(mpnn_kernel<0>, cudaFuncAttributeMaxDynamicSharedMemorySize, SMEM_BYTES);
        cudaFuncSetAttribute(mpnn_kernel<1>, cudaFuncAttributeMaxDynamicSharedMemorySize, SMEM_BYTES);
        cudaFuncSetAttribute(mpnn_kernel<2>, cudaFuncAttributeMaxDynamicSharedMemorySize, SMEM_BYTES);
        int dev = 0, sms = 0, occ = 0;
        cudaGetDevice(&dev);
        cudaDeviceGetAttribute(&sms, cudaDevAttrMultiProcessorCount, dev);
        cudaOccupancyMaxActiveBlocksPerMultiprocessor(&occ, mpnn_kernel<0>, NT, SMEM_BYTES);
        void* fn = nullptr;
        cudaDriverEntryPointQueryResult qr;
        cudaGetDriverEntryPoint("cuTensorMapEncodeTiled", &fn, cudaEnableDefault, &qr);
        enc = (EncodeTiledFn)fn;
        cudaGetSymbolAddress(&p_addr, g_P);
        cudaGetSymbolAddress(&c_addr, g_cells);
        cudaGetSymbolAddress(&bar_addr, g_bar);
        fused = (sms * occ >= G) ? 1 : 0;
    }
    CUtensorMap tx, tw1, tp, tw2, tout;
    make_map(enc, &tx, d_in[0], 128, N_NODES, 80);
    make_map(enc, &tw1, d_in[4], 256, 257, 128);
    make_map(enc, &tp, p_addr, 256, N_NODES, NB);
    make_map(enc, &tw2, d_in[6], 128, 256, 256);
    make_map(enc, &tout, d_out, 128, N_NODES, NB);
    cudaStream_t st = cudaStreamPerThread;
#define MPNN_ARGS (const int2*)d_in[3], (const int2*)d_in[2], (const uint32_t*)d_in[1], (uint4*)c_addr, \
    (const char*)p_addr, (GridBar*)bar_addr, (const char*)d_in[4], (const char*)d_in[5], (const char*)d_in[7], tx, tw1, tp, tw2, tout
    if (fused) {
        mpnn_kernel<0><<<G, NT, SMEM_BYTES, st>>>(MPNN_ARGS);
    } else {
        mpnn_kernel<1><<<G, NT, SMEM_BYTES, st>>>(MPNN_ARGS);
        mpnn_kernel<2><<<G, NT, SMEM_BYTES, st>>>(MPNN_ARGS);
    }
}
```

```cpp
#include <cuda_runtime.h>
#include <cuda_bf16.h>
#include <cuda.h>
#include <stdint.h>

namespace {

constexpr int N_NODES = 10000;
constexpr int N_EDGES = 160000;
constexpr int G = 132;
constexpr int NB = 76;
constexpr int EPB = 1216;
constexpr int CPC = 10;
constexpr int CELL_CAP = 3 * CPC;
constexpr int NCHUNK = G * CPC;
constexpr int CAP = 2560;
constexpr int DUMMY_ID = 79;

constexpr uint32_t HALF2 = 0x3f003f00u;
constexpr int CELL_DELAY = 2000;
constexpr int NW = 24;
constexpr int NT = NW * 32;
constexpr int U = 2;
constexpr int GR = 2;

constexpr int SM_W0 = 0;
constexpr int SM_W1 = 65536;
constexpr int SM_X = 131072;
constexpr int FLEN = CAP + 32;
constexpr int SM_LIST = 151552;
constexpr int SM_STAGE = SM_LIST + FLEN * 8;
constexpr int SM_CONST = SM_STAGE + NCHUNK * 16;
constexpr int SM_CCNT = SM_CONST + 1280;
static_assert(SM_LIST + G * CELL_CAP * 8 <= SM_CONST && SM_STAGE % 128 == 0, "list overrun");
constexpr int SM_NCNT = SM_CCNT + 136 * 4;
constexpr int SM_OCNT = SM_NCNT + 160 * 4;
constexpr int SM_OCUR = SM_OCNT + 96 * 4;
constexpr int SM_MISC = SM_OCUR + 96 * 4;
constexpr int SM_ZEND = SM_MISC + 12 * 4;
constexpr int SM_OFF = SM_ZEND;
constexpr int SM_DEG = SM_OFF + 160 * 4;
constexpr int SM_LAUNCH = SM_DEG + 96 * 4;
constexpr int SM_MBAR = SM_LAUNCH + 8;
constexpr int SM_END = SM_MBAR + 32 * 8;
constexpr int SMEM_BYTES = SM_END + 1024;
static_assert(SM_MBAR % 8 == 0, "align");
static_assert(SM_LIST % 16 == 0 && SM_NCNT % 16 == 0 && SM_OFF % 16 == 0 && SM_CONST % 16 == 0, "align");
constexpr int WS = NW - 1;
constexpr int LT = WS * 32;
constexpr int WPS = NW / 4;
constexpr int WA = 25, WB = 4;
constexpr int WTOT = WA * WS + WB * (WPS - 1);

struct __align__(128) GridBar { unsigned int v; unsigned int pad[31]; };

__device__ __align__(1024) uint4 g_P[G * NB * 32];
__device__ __align__(1024) uint4 g_cells[G * NCHUNK];
__device__ uint2 g_ovf[G * EPB];
__device__ int g_ovfn[G];
__device__ float g_acc[G * NB * 256];
__device__ GridBar g_bar;

__device__ __forceinline__ float tanh_fast(float x) { float y; asm("tanh.approx.f32 %0, %1;" : "=f"(y) : "f"(x)); return y; }
__device__ __forceinline__ uint32_t pack_bf16(float lo, float hi) { uint32_t r; asm("cvt.rn.bf16x2.f32 %0, %1, %2;" : "=r"(r) : "f"(hi), "f"(lo)); return r; }
__device__ __forceinline__ uint32_t hfma2_hi(uint32_t a, uint32_t b, uint32_t c) {
    uint32_t r;
    asm("{.reg .b16 l, h; .reg .b32 t; mov.b32 {l, h}, %1; mov.b32 t, {h, h}; fma.rn.bf16x2 %0, t, %2, %3;}" : "=r"(r) : "r"(a), "r"(b), "r"(c));
    return r;
}
__device__ __forceinline__ uint32_t add_half(uint32_t a, uint32_t b) { uint32_t r; asm("fma.rn.bf16x2 %0, %2, %3, %1;" : "=r"(r) : "r"(a), "r"(b), "r"(0x3f003f00u)); return r; }
__device__ __forceinline__ uint32_t hmul2(uint32_t a, uint32_t b) { uint32_t r; asm("mul.rn.bf16x2 %0, %1, %2;" : "=r"(r) : "r"(a), "r"(b)); return r; }
__device__ __forceinline__ float bf_lo(uint32_t v) { return __uint_as_float(v << 16); }
__device__ __forceinline__ float bf_lo_alu(uint32_t v) { uint32_t t; asm("prmt.b32 %0, %1, 0, 0x1044;" : "=r"(t) : "r"(v)); return __uint_as_float(t); }
__device__ __forceinline__ float bf_hi(uint32_t v) { return __uint_as_float(v & 0xffff0000u); }
__device__ __forceinline__ uint4 lds128(uint32_t a) { uint4 v; asm volatile("ld.shared.v4.u32 {%0,%1,%2,%3}, [%4];" : "=r"(v.x), "=r"(v.y), "=r"(v.z), "=r"(v.w) : "r"(a) : "memory"); return v; }
__device__ __forceinline__ uint2 lds64(uint32_t a) { uint2 v; asm volatile("ld.shared.v2.u32 {%0,%1}, [%2];" : "=r"(v.x), "=r"(v.y) : "r"(a) : "memory"); return v; }
__device__ __forceinline__ uint32_t lds32(uint32_t a) { uint32_t v; asm volatile("ld.shared.u32 %0, [%1];" : "=r"(v) : "r"(a) : "memory"); return v; }
__device__ __forceinline__ uint32_t lds8(uint32_t a) { uint32_t v; asm volatile("ld.shared.u8 %0, [%1];" : "=r"(v) : "r"(a) : "memory"); return v; }
__device__ __forceinline__ void sts128(uint32_t a, uint32_t x, uint32_t y, uint32_t z, uint32_t w) { asm volatile("st.shared.v4.u32 [%0], {%1,%2,%3,%4};" :: "r"(a), "r"(x), "r"(y), "r"(z), "r"(w) : "memory"); }
__device__ __forceinline__ void sts32(uint32_t a, uint32_t x) { asm volatile("st.shared.u32 [%0], %1;" :: "r"(a), "r"(x) : "memory"); }
__device__ __forceinline__ void sts8(uint32_t a, uint32_t x) { asm volatile("st.shared.u8 [%0], %1;" :: "r"(a), "r"(x) : "memory"); }
__device__ __forceinline__ uint32_t atoms_inc(uint32_t a) { uint32_t r; asm volatile("atom.shared.add.u32 %0, [%1], 1;" : "=r"(r) : "r"(a) : "memory"); return r; }
__device__ __forceinline__ void stg128(void* p, const uint4& v) { asm volatile("st.global.v4.u32 [%0], {%1,%2,%3,%4};" :: "l"(p), "r"(v.x), "r"(v.y), "r"(v.z), "r"(v.w) : "memory"); }
__device__ __forceinline__ uint4 ldg128_l2(const void* p) { uint4 v; asm volatile("ld.relaxed.gpu.global.v4.u32 {%0,%1,%2,%3}, [%4];" : "=r"(v.x), "=r"(v.y), "=r"(v.z), "=r"(v.w) : "l"(p) : "memory"); return v; }
__device__ __forceinline__ void tma_load(uint32_t dst, const CUtensorMap* m, int row, int blk, uint32_t bar) {
    asm volatile("cp.async.bulk.tensor.3d.shared::cluster.global.mbarrier::complete_tx::bytes [%0], [%1, {0, %2, %3}], [%4];" :: "r"(dst), "l"(m), "r"(row), "r"(blk), "r"(bar) : "memory");
}
__device__ __forceinline__ void tma_store(const CUtensorMap* m, int row, int blk, uint32_t srcaddr) {
    asm volatile("cp.async.bulk.tensor.3d.global.shared::cta.bulk_group [%0, {0, %1, %2}], [%3];" :: "l"(m), "r"(row), "r"(blk), "r"(srcaddr) : "memory");
}
__device__ __forceinline__ void bulk_load(uint32_t dst, const void* p, uint32_t bytes, uint32_t bar) {
    asm volatile("cp.async.bulk.shared::cluster.global.mbarrier::complete_tx::bytes [%0], [%1], %2, [%3];" :: "r"(dst), "l"(p), "r"(bytes), "r"(bar) : "memory");
}
__device__ __forceinline__ void prefetch_map(const CUtensorMap* m) { asm volatile("prefetch.tensormap [%0];" :: "l"(m) : "memory"); }
__device__ __forceinline__ bool elect_one() {
    uint32_t p;
    asm volatile("{.reg .pred p; elect.sync _|p, 0xffffffff; selp.u32 %0, 1, 0, p;}" : "=r"(p));
    return p != 0;
}
__device__ __forceinline__ uint32_t lds16(uint32_t a) { uint32_t v; asm volatile("ld.shared.u16 %0, [%1];" : "=r"(v) : "r"(a) : "memory"); return v; }
__device__ __forceinline__ void smem_wait(uint32_t a) {
    asm volatile("{.reg .pred p, q; .reg .u32 n, v; mov.u32 n, 0;\n"
                 "W%=: ld.acquire.cta.shared.u32 v, [%0]; setp.eq.u32 p, v, 0;\n"
                 "add.u32 n, n, 1; setp.lt.u32 q, n, 0x4000000; and.pred q, q, p; @q bra W%=;}" :: "r"(a) : "memory");
}
__device__ __forceinline__ uint32_t clock32() { uint32_t t; asm volatile("mov.u32 %0, %clock;" : "=r"(t)); return t; }
__device__ __forceinline__ void wait_until(uint32_t t) {
    asm volatile("{.reg .pred p; .reg .s32 d; .reg .u32 c;\n"
                 "U%=: mov.u32 c, %clock; sub.s32 d, c, %0; setp.lt.s32 p, d, 0; @p nanosleep.u32 20; @p bra U%=;}" :: "r"(t) : "memory");
}
__device__ __forceinline__ void expect_tx(uint32_t bar, uint32_t bytes) { asm volatile("mbarrier.arrive.expect_tx.shared::cta.b64 _, [%0], %1;" :: "r"(bar), "r"(bytes) : "memory"); }
__device__ __forceinline__ bool bar_or(int id, int n, bool p) {
    uint32_t r;
    asm volatile("{.reg .pred p, q; setp.ne.u32 p, %3, 0; bar.red.or.pred q, %1, %2, p; selp.u32 %0, 1, 0, q;}" : "=r"(r) : "r"(id), "r"(n), "r"((uint32_t)p) : "memory");
    return r != 0;
}
__device__ __forceinline__ void mbar_wait(uint32_t bar) {
    asm volatile("{.reg .pred p, q; .reg .u32 n; mov.u32 n, 0;\n"
                 "W%=: mbarrier.try_wait.parity.shared::cta.b64 p, [%0], 0;\n"
                 "add.u32 n, n, 1; setp.lt.u32 q, n, 0x100000; and.pred q, q, !p; @q bra W%=;}" :: "r"(bar) : "memory");
}
__device__ __forceinline__ void fence_async() { asm volatile("fence.proxy.async.shared::cta;" ::: "memory"); }
__device__ __forceinline__ void bar_sync(int id, int n) { asm volatile("bar.sync %0, %1;" :: "r"(id), "r"(n) : "memory"); }
__device__ __forceinline__ void bar_arrive(int id, int n) { asm volatile("bar.arrive %0, %1;" :: "r"(id), "r"(n) : "memory"); }
__device__ __forceinline__ void stsm4t(uint32_t a, uint32_t r0, uint32_t r1, uint32_t r2, uint32_t r3) {
    asm volatile("stmatrix.sync.aligned.m8n8.x4.trans.shared.b16 [%0], {%1,%2,%3,%4};" :: "r"(a), "r"(r0), "r"(r1), "r"(r2), "r"(r3) : "memory");
}
__device__ __forceinline__ uint32_t desc_lo(uint32_t addr) { return __shfl_sync(0xffffffffu, ((addr & 0x3FFFF) >> 4) | 0x10000u, 0); }
template <int ACC>
__device__ __forceinline__ void wgmma80(float* d, uint32_t la, uint32_t lb) {
    asm volatile("{.reg .pred p; .reg .b64 da, db; setp.ne.b32 p, %42, 0;\n"
        "mov.b64 da, {%40, 0x40000040}; mov.b64 db, {%41, 0x40000040};\n"
        "wgmma.mma_async.sync.aligned.m64n80k16.f32.bf16.bf16 "
        "{%0,%1,%2,%3,%4,%5,%6,%7,%8,%9,%10,%11,%12,%13,%14,%15,%16,%17,%18,%19,"
        "%20,%21,%22,%23,%24,%25,%26,%27,%28,%29,%30,%31,%32,%33,%34,%35,%36,%37,%38,%39}, da, db, p, 1, 1, 1, 0;}\n"
        : "+f"(d[0]), "+f"(d[1]), "+f"(d[2]), "+f"(d[3]), "+f"(d[4]), "+f"(d[5]), "+f"(d[6]), "+f"(d[7]), "+f"(d[8]), "+f"(d[9]),
          "+f"(d[10]), "+f"(d[11]), "+f"(d[12]), "+f"(d[13]), "+f"(d[14]), "+f"(d[15]), "+f"(d[16]), "+f"(d[17]), "+f"(d[18]), "+f"(d[19]),
          "+f"(d[20]), "+f"(d[21]), "+f"(d[22]), "+f"(d[23]), "+f"(d[24]), "+f"(d[25]), "+f"(d[26]), "+f"(d[27]), "+f"(d[28]), "+f"(d[29]),
          "+f"(d[30]), "+f"(d[31]), "+f"(d[32]), "+f"(d[33]), "+f"(d[34]), "+f"(d[35]), "+f"(d[36]), "+f"(d[37]), "+f"(d[38]), "+f"(d[39])
        : "r"(la), "r"(lb), "n"(ACC) : "memory");
}
template <int KS, int BSTRIDE, int SPLIT>
__device__ __forceinline__ void gemm80(float* d, uint32_t la, uint32_t lb) {
    asm volatile("wgmma.fence.sync.aligned;" ::: "memory");
    wgmma80<0>(d, la, lb);
#pragma unroll
    for (int s = 1; s < KS; s++) {
        if (SPLIT && s == KS - SPLIT) asm volatile("wgmma.commit_group.sync.aligned;" ::: "memory");
        wgmma80<1>(d, la + s * 128, lb + (s >> 2) * (BSTRIDE / 16) + (s & 3) * 2);
    }
    asm volatile("wgmma.commit_group.sync.aligned;" ::: "memory");
    if (SPLIT) asm volatile("wgmma.wait_group.sync.aligned 1;" ::: "memory");
}
__device__ __forceinline__ void wg_wait(float* d) {
    asm volatile("wgmma.wait_group.sync.aligned 0;" ::: "memory");
#pragma unroll
    for (int i = 0; i < 40; i++) asm volatile("" : "+f"(d[i]) :: "memory");
}
__device__ __forceinline__ void grid_arrive(GridBar* b) {
    asm volatile("red.relaxed.gpu.global.add.u32 [%0], %1;" :: "l"(&b->v), "r"(blockIdx.x == 0 ? 256u - (G - 1) : 1u) : "memory");
}
__device__ __forceinline__ uint32_t grid_peek(GridBar* b) {
    uint32_t v;
    asm volatile("ld.relaxed.gpu.global.u32 %0, [%1];" : "=r"(v) : "l"(&b->v) : "memory");
    return v;
}
__device__ __forceinline__ void grid_wait(GridBar* b, uint32_t peek) {
    asm volatile("{.reg .pred p, q; .reg .u32 n, v; mov.u32 n, 0;\n"
                 "W%=: ld.acquire.gpu.global.u32 v, [%0]; xor.b32 v, v, %1; setp.lt.u32 p, v, 256;\n"
                 "add.u32 n, n, 1; setp.lt.u32 q, n, 0x400000; and.pred q, q, p; @q bra W%=;}" :: "l"(&b->v), "r"(peek) : "memory");
}

constexpr int BAR_READY = 1, BAR_INIT = 2, BAR_CELLS = 3, BAR_WG0 = 4, BAR_P0 = 8, BAR_CHAIN0 = 12;
constexpr int MB_WA = 0, MB_WB = 1, MB_X = 2, MB_C = 3, MB_W2 = 4, MB_CELL = 5, MB_PART = 8;

__device__ __forceinline__ uint32_t frag_offset(int lane, int wq) {
    return (uint32_t)(((lane & 7) + 8 * (lane >> 4)) * 128 + (((2 * wq + ((lane >> 3) & 1)) ^ (lane & 7)) << 4));
}
template <class F>
__device__ __forceinline__ void for_overflow(uint32_t sb, int node0, int first, int stride, F f) {
#pragma unroll 1
    for (int m = 0; m < 5; m++) {
        uint32_t bits = lds32(sb + SM_MISC + m * 4);
#pragma unroll 1
        while (bits) {
            const int s = m * 32 + __ffs(bits) - 1;
            bits &= bits - 1;
            const int n = __ldcg(&g_ovfn[s]);
#pragma unroll 4
            for (int i = first; i < n; i += stride) {
                const uint2 en = __ldcg(&g_ovf[s * EPB + i]);
                const uint32_t id = en.x - (uint32_t)node0;
                if (id < (uint32_t)NB) f(id, en.y);
            }
        }
    }
}

__device__ __forceinline__ void put_entry(uint32_t base, uint32_t pos, uint32_t id, uint32_t word) {
    asm volatile("st.shared.v2.u32 [%0], {%1, %2};" :: "r"(base + pos * 8), "r"(word & 0xffffu), "r"((word & 0xffff0000u) | id) : "memory");
}
__device__ __forceinline__ void put_valid(uint32_t base, uint32_t pos, uint32_t id, uint32_t word) {
    asm volatile("{.reg .pred p; setp.lt.u32 p, %3, 128; @p st.shared.v2.u32 [%0], {%1, %2};}"
                 :: "r"(base + pos * 8), "r"(word & 0xffffu), "r"((word & 0xffff0000u) | id), "r"(id) : "memory");
}
__device__ __noinline__ void cold_spill(uint32_t sb, uint32_t dv, uint32_t word) {
    const uint32_t o = atoms_inc(sb + SM_MISC + 5 * 4);
    g_ovf[blockIdx.x * EPB + o] = make_uint2(dv, word);
    sts8(sb + SM_STAGE + (dv / NB) * (CPC * 16) + 15, 0u);
}
__device__ __noinline__ void cold_spill_publish(uint32_t sb) {
    if (threadIdx.x == 0) g_ovfn[blockIdx.x] = (int)lds32(sb + SM_MISC + 5 * 4);
    __threadfence();
    bar_sync(BAR_READY, LT);
}
__device__ __noinline__ void cold_mark(uint32_t sb, int s) {
    sts32(sb + SM_MISC + 6 * 4, 1u);
    asm volatile("red.shared.or.b32 [%0], %1;" :: "r"(sb + SM_MISC + (s >> 5) * 4), "r"(1u << (s & 31)) : "memory");
}
__device__ __noinline__ void cold_count(uint32_t sb, int lt) {
    __threadfence();
    for_overflow(sb, blockIdx.x * NB, lt, 32, [&](uint32_t id, uint32_t) { atoms_inc(sb + SM_OCNT + id * 4); });
    __syncwarp();
}
__device__ __noinline__ void cold_put(uint32_t sb, int lt) {
    for_overflow(sb, blockIdx.x * NB, lt, 32, [&](uint32_t id, uint32_t word) {
        put_entry(sb + SM_LIST, lds32(sb + SM_OFF + id * 4) + lds32(sb + SM_NCNT + id * 4) + atoms_inc(sb + SM_OCUR + id * 4), id, word);
    });
}
__device__ __noinline__ void cold_direct(uint32_t sb, const uint4* cells, const char* P) {
    const int tid = threadIdx.x, lane = tid & 31, w = tid >> 5, node0 = blockIdx.x * NB;
    auto row_addr = [&](uint32_t id) { return sb + SM_W1 + (lane >> 3) * 16384 + id * 128 + (((lane ^ id) & 7) << 4); };
    const uint4 wc = lds128(sb + SM_CONST + lane * 16);
    smem_wait(sb + SM_MISC + 7 * 4);
    float* accg = g_acc + (size_t)node0 * 256;
#pragma unroll 1
    for (int i = tid; i < NB * 256; i += NT - 32) accg[i] = 0.f;
    bar_sync(BAR_READY, NT - 32);
    auto one = [&](uint32_t id, uint32_t word) {
        const uint4 p = ldg128_l2(P + lane * 16 + (size_t)(word & 0xffffu) * 512), q = lds128(row_addr(id));
        const uint32_t z[4] = {add_half(hfma2_hi(word, hmul2(wc.x, HALF2), q.x), p.x), add_half(hfma2_hi(word, hmul2(wc.y, HALF2), q.y), p.y),
                               add_half(hfma2_hi(word, hmul2(wc.z, HALF2), q.z), p.z), add_half(hfma2_hi(word, hmul2(wc.w, HALF2), q.w), p.w)};
#pragma unroll
        for (int j = 0; j < 4; j++) {
            const float a = bf_lo(z[j]), b = bf_hi(z[j]);
            atomicAdd(accg + id * 256 + lane * 8 + 2 * j, fmaf(a, tanh_fast(a), a));
            atomicAdd(accg + id * 256 + lane * 8 + 2 * j + 1, fmaf(b, tanh_fast(b), b));
        }
    };
#pragma unroll 1
    for (int c = w * 3; c < NCHUNK * 3; c += (c % 3 == 2) ? WS * 3 - 2 : 1) {
        const uint32_t* cell = (const uint32_t*)(cells + blockIdx.x * NCHUNK + c / 3);
        const uint32_t id = (__ldcg(cell + 3) >> (8 * (c % 3))) & 0xffu;
        if (id < 128u) one(id, __ldcg(cell + c % 3));
    }
    for_overflow(sb, node0, w, WS, one);
    __threadfence();
    bar_sync(BAR_READY, NT - 32);
#pragma unroll 1
    for (int n = w; n < NB; n += WS) {
        float a[8];
#pragma unroll
        for (int j = 0; j < 8; j++) a[j] = __ldcg(accg + n * 256 + lane * 8 + j);
        sts128(row_addr(n), pack_bf16(a[0], a[1]), pack_bf16(a[2], a[3]), pack_bf16(a[4], a[5]), pack_bf16(a[6], a[7]));
    }
}

template <int PHASE>
__global__ void __launch_bounds__(NT, 1)
mpnn_kernel(const int2* __restrict__ dst, const int2* __restrict__ src, const uint32_t* __restrict__ ea,
            uint4* cells, const char* P, GridBar* bar, const char* __restrict__ w1, const char* __restrict__ b1, const char* __restrict__ b2,
            const __grid_constant__ CUtensorMap tm_x, const __grid_constant__ CUtensorMap tm_w1, const __grid_constant__ CUtensorMap tm_p,
            const __grid_constant__ CUtensorMap tm_w2, const __grid_constant__ CUtensorMap tm_out) {
    extern __shared__ char smem_raw[];
    int2 e_dst = make_int2(0, 0), e_src = make_int2(0, 0);
    uint32_t e_att = 0;
    bool e_ok = false;
    if (PHASE != 2) {
        const uint32_t i2 = threadIdx.x - 128u, e2 = blockIdx.x * (EPB / 2) + i2;
        e_ok = i2 < EPB / 2 && e2 < N_EDGES / 2;
        if (e_ok) {
            asm volatile("ld.global.nc.v2.u32 {%0,%1}, [%2];" : "=r"(e_dst.x), "=r"(e_dst.y) : "l"(dst + e2));
            asm volatile("ld.global.nc.v2.u32 {%0,%1}, [%2];" : "=r"(e_src.x), "=r"(e_src.y) : "l"(src + e2));
            asm volatile("ld.global.nc.u32 %0, [%1];" : "=r"(e_att) : "l"(ea + e2));
        }
    }
    const uint32_t sb = ((uint32_t)__cvta_generic_to_shared(smem_raw) + 1023u) & ~1023u;
    const uint32_t mb = sb + SM_MBAR;
    const int tid = threadIdx.x, lane = tid & 31;
    const int w = __shfl_sync(0xffffffffu, tid >> 5, 0);
    const int cta = blockIdx.x;
    const int node0 = cta * NB;

    const int wg = w >> 2, wq = w & 3;
    float d[40];
    if (w == WS) {
        const bool el = elect_one();
        if (el) {
#pragma unroll
            for (int i = 0; i < 6; i++) asm volatile("mbarrier.init.shared::cta.b64 [%0], 1;" :: "r"(mb + i * 8) : "memory");
            asm volatile("fence.mbarrier_init.release.cluster;" ::: "memory");
            prefetch_map(&tm_w1); prefetch_map(&tm_x);
        }
        __syncwarp();
        bar_arrive(BAR_INIT, NT);
        if (el) {
            if (PHASE != 2) {
                expect_tx(mb + MB_WA * 8, 65536);
                tma_load(sb + SM_W0, &tm_w1, 0, 0, mb + MB_WA * 8);
            }
            expect_tx(mb + MB_X * 8, 20480);
            tma_load(sb + SM_X, &tm_x, node0, 0, mb + MB_X * 8);
            if (PHASE != 1) {
                expect_tx(mb + MB_WB * 8, 65536);
                tma_load(sb + SM_W1, &tm_w1, 128, 0, mb + MB_WB * 8);
            }
            expect_tx(mb + MB_C * 8, 1280);
            bulk_load(sb + SM_CONST, w1 + 256 * 512, 512, mb + MB_C * 8);
            bulk_load(sb + SM_CONST + 512, b1, 512, mb + MB_C * 8);
            bulk_load(sb + SM_CONST + 1024, b2, 256, mb + MB_C * 8);
            prefetch_map(&tm_p); prefetch_map(&tm_w2); prefetch_map(&tm_out);
#pragma unroll 1
            for (int i = 0; i < WS; i++) asm volatile("mbarrier.init.shared::cta.b64 [%0], 32;" :: "r"(mb + (MB_PART + i) * 8) : "memory");
        }
        __syncwarp();
        if (PHASE == 0) bar_sync(BAR_CELLS, NT);
        const uint32_t t_cells = clock32() + CELL_DELAY;
        auto fetch_cells = [&]() {
            fence_async();
            if (PHASE == 0) wait_until(t_cells);
            expect_tx(mb + MB_CELL * 8, NCHUNK * 16);
            bulk_load(sb + SM_STAGE, cells + cta * NCHUNK, NCHUNK * 16, mb + MB_CELL * 8);
        };
        if (PHASE == 2) { if (el) fetch_cells(); __syncwarp(); }
        if (PHASE != 2) {
#pragma unroll 1
            for (int j = 0; j < 4; j++) {
                bar_sync(BAR_P0 + j, 160);
                if (el) {
                    tma_store(&tm_p, node0, j, sb + SM_W0 + j * 16384);
                    if (PHASE == 0 && j == 0) fetch_cells();
                }
                __syncwarp();
            }
        }
        if (el) {
            if (PHASE != 2) {
                asm volatile("cp.async.bulk.commit_group;" ::: "memory");
                asm volatile("cp.async.bulk.wait_group.read 0;" ::: "memory");
            }
            if (PHASE != 1) {
                expect_tx(mb + MB_W2 * 8, 65536);
                tma_load(sb + SM_W0, &tm_w2, 0, 0, mb + MB_W2 * 8);
            }
            if (PHASE != 2) {
                asm volatile("cp.async.bulk.wait_group 0;" ::: "memory");
                asm volatile("fence.acq_rel.gpu;" ::: "memory");
                grid_arrive(bar);
            }
            if (PHASE == 0) grid_wait(bar, lds32(sb + SM_LAUNCH));
            asm volatile("st.release.cta.shared.u32 [%0], 1;" :: "r"(sb + SM_MISC + 7 * 4) : "memory");
        }
        __syncwarp();
        if (PHASE != 1) {
            smem_wait(sb + SM_MISC + 8 * 4);
            const uint32_t a = sb + SM_NCNT + min(lane, 23) * 16;
            const uint4 c = lds128(a), o = lds128(a + (SM_OCNT - SM_NCNT));
            const uint32_t c4[4] = {c.x + o.x, c.y + o.y, c.z + o.z, c.w + o.w};
            if (lane < 24) sts128(sb + SM_DEG + lane * 16, __float_as_uint((float)c4[0]), __float_as_uint((float)c4[1]), __float_as_uint((float)c4[2]), __float_as_uint((float)c4[3]));
#pragma unroll
            for (int p = 0; p < 4; p++) {
                uint32_t z = __ballot_sync(0xffffffffu, lane < NB / 4 && c4[p] == 0u);
#pragma unroll 1
                while (z) {
                    const uint32_t id = (__ffs(z) - 1) * 4 + p;
                    sts128(sb + SM_W1 + (lane >> 3) * 16384 + id * 128 + (((lane ^ id) & 7) << 4), 0u, 0u, 0u, 0u);
                    z &= z - 1;
                }
            }
            fence_async();
        }
    } else {
    constexpr int TWO = NCHUNK - LT;
    static_assert(TWO > 0 && TWO <= LT, "chunks");
    uint32_t peek = 0;
    if (tid == 0) peek = grid_peek(bar);
    if (PHASE != 2) {
        auto empty = [&](uint32_t k) {
            return 0x80000000u | (128u + ((k < 4 ? cta * 4 + k : 4 * G + cta * (CPC - 4) + k - 4) & 31u)) * 0x010101u;
        };
        sts32(sb + SM_STAGE + tid * 16 + 12, empty((uint32_t)tid % CPC));
        if (tid < TWO) sts32(sb + SM_STAGE + (LT + tid) * 16 + 12, empty((uint32_t)(LT + tid) % CPC));
    }
    if (tid < (SM_ZEND - SM_CCNT) / 4) sts32(sb + SM_CCNT + tid * 4, 0u);
    static_assert((SM_ZEND - SM_CCNT) / 4 <= LT && LT - 128 >= EPB / 2, "zeroing");
    bar_sync(BAR_INIT, NT);
    if (tid == 0) sts32(sb + SM_LAUNCH, peek);
    const uint32_t frag_off = frag_offset(lane, wq);
    const uint32_t slab = sb + SM_W0 + wg * 16384;
    const uint32_t la = desc_lo(slab), lb = desc_lo(sb + SM_X);
    uint4* out0 = cells + ((uint32_t)tid / CPC) * (NCHUNK - CPC) + cta * CPC + tid;
    uint4* out1 = cells + ((uint32_t)(tid + LT) / CPC) * (NCHUNK - CPC) + cta * CPC + tid + LT;
    bool spilled = false;
    if (PHASE != 2) {
        if (e_ok) {
            const uint32_t z = lds32(sb + SM_MISC + 9 * 4);
            const uint32_t dv[2] = {(uint32_t)e_dst.x | z, (uint32_t)e_dst.y | z};
            const uint32_t wd[2] = {__byte_perm((uint32_t)e_src.x, e_att | z, 0x5410), __byte_perm((uint32_t)e_src.y, e_att | z, 0x7610)};
            uint32_t oc[2], r[2];
#pragma unroll
            for (int k = 0; k < 2; k++) { oc[k] = dv[k] / NB; r[k] = atoms_inc(sb + SM_CCNT + oc[k] * 4); }
#pragma unroll
            for (int k = 0; k < 2; k++) {
                const uint32_t ch = (r[k] * 11) >> 5, p = r[k] - ch * 3;
                const uint32_t a = sb + SM_STAGE + oc[k] * (CPC * 16) + ch * 16;
                asm volatile("{.reg .pred p; setp.lt.u32 p, %4, %5; @p st.shared.u32 [%0], %1; @p st.shared.u8 [%2], %3;}"
                             :: "r"(a + p * 4), "r"(wd[k]), "r"(a + 12 + p), "r"(dv[k] - oc[k] * NB), "r"(r[k]), "n"(CELL_CAP) : "memory");
            }
            if (__builtin_expect(max(r[0], r[1]) >= CELL_CAP, 0)) {
                if (r[0] >= CELL_CAP) cold_spill(sb, dv[0], wd[0]);
                if (r[1] >= CELL_CAP) cold_spill(sb, dv[1], wd[1]);
                spilled = true;
            }
        }
    }
    if (__builtin_expect(bar_or(BAR_READY, LT, spilled), 0)) cold_spill_publish(sb);
    const uint32_t launch = (lds32(sb + SM_LAUNCH) - (PHASE == 2 ? 256u : 0u)) >> 8;
    const uint32_t ctag = (launch & 63u) + 1u;
    const uint32_t ptag = (launch + 1u) & 1u;
    if (PHASE != 2) {
        uint4 v = lds128(sb + SM_STAGE + tid * 16);
        v.w |= ctag << 24;
        stg128(out0, v);
        if (tid < TWO) {
            v = lds128(sb + SM_STAGE + (LT + tid) * 16);
            v.w |= ctag << 24;
            stg128(out1, v);
        }
        if (PHASE == 0) bar_arrive(BAR_CELLS, NT);
        if (w < 16) {
            mbar_wait(mb + MB_X * 8);
            mbar_wait(mb + MB_WA * 8);
            if (wg > 0) bar_sync(BAR_CHAIN0 + wg - 1, 256);
            gemm80<8, 10240, 2>(d, la, lb);
            if (wg < 3) bar_arrive(BAR_CHAIN0 + wg, 256);
            const uint32_t keep = (lane < 4) ? 0xfffefffeu : 0xffffffffu, set = (lane < 4) ? ptag * 0x00010001u : 0u;
            wg_wait(d);
            bar_sync(BAR_WG0 + wg, 128);
#pragma unroll
            for (int i = 0; i < 5; i++)
                stsm4t(slab + i * 2048 + frag_off,
                       (pack_bf16(d[8 * i + 0], d[8 * i + 1]) & keep) | set, (pack_bf16(d[8 * i + 2], d[8 * i + 3]) & keep) | set,
                       (pack_bf16(d[8 * i + 4], d[8 * i + 5]) & keep) | set, (pack_bf16(d[8 * i + 6], d[8 * i + 7]) & keep) | set);
            fence_async();
            bar_arrive(BAR_P0 + wg, 160);
        }
    }
    if (PHASE != 1) {
    const uint32_t c0 = tid < 4 * G ? (tid >> 2) * CPC + (tid & 3) : ((uint32_t)(tid - 4 * G) / (CPC - 4)) * 4 + 4 + tid - 4 * G;
    const uint32_t c1 = ((uint32_t)(tid + LT - 4 * G) / (CPC - 4)) * 4 + 4 + tid + LT - 4 * G;
    if (w < 16) {
        if (PHASE == 2) mbar_wait(mb + MB_X * 8);
        mbar_wait(mb + MB_WB * 8);
        gemm80<8, 10240, 0>(d, la + 4096, lb);
        mbar_wait(mb + MB_C * 8);
        const uint32_t ba = sb + SM_CONST + 512 + (w * 16 + (lane >> 2)) * 2;
        const float bl = 0.5f * bf_lo(lds16(ba)), bh = 0.5f * bf_lo(lds16(ba + 16));
        wg_wait(d);
        bar_sync(BAR_WG0 + wg, 128);
#pragma unroll
        for (int i = 0; i < 5; i++)
            stsm4t(slab + 65536 + i * 2048 + frag_off,
                   pack_bf16(fmaf(d[8 * i + 0], 0.5f, bl), fmaf(d[8 * i + 1], 0.5f, bl)), pack_bf16(fmaf(d[8 * i + 2], 0.5f, bh), fmaf(d[8 * i + 3], 0.5f, bh)),
                   pack_bf16(fmaf(d[8 * i + 4], 0.5f, bl), fmaf(d[8 * i + 5], 0.5f, bl)), pack_bf16(fmaf(d[8 * i + 6], 0.5f, bh), fmaf(d[8 * i + 7], 0.5f, bh)));
    } else mbar_wait(mb + MB_C * 8);
    const uint32_t lane16 = lane * 16;
    uint32_t sH = sb + SM_W1 + (lane >> 3) * 16384;
    uint32_t lsw = lane16 & 0x70;
    auto row_addr = [&](uint32_t id) { return sH + id * 128 + (lsw ^ ((id << 4) & 0x70)); };
    int T;
    {
        uint4 cv[2];
        mbar_wait(mb + MB_CELL * 8);
        cv[0] = lds128(sb + SM_STAGE + c0 * 16);
        cv[1].w = 0x80000000u | (ctag << 24) | (128u + lane) * 0x010101u;
        if (tid < TWO) cv[1] = lds128(sb + SM_STAGE + c1 * 16);
        const uint32_t tg = ctag << 24;
        uint32_t m = __reduce_or_sync(0xffffffffu, (((cv[0].w ^ tg) | (cv[1].w ^ tg)) & 0x7f000000u) | (~cv[0].w & 0x80000000u) | (~cv[1].w & 0x80u));
        if (__builtin_expect(m > 0xffu, 0)) {
#pragma unroll 1
            for (int it = 0;; it++) {
                const bool s0 = ((cv[0].w ^ tg) & 0x7f000000u) != 0u, s1 = ((cv[1].w ^ tg) & 0x7f000000u) != 0u;
                if (!__any_sync(0xffffffffu, (s0 || s1) && it < (1 << 22))) break;
                if (s0) cv[0] = ldg128_l2(cells + cta * NCHUNK + c0);
                if (s1) cv[1] = ldg128_l2(cells + cta * NCHUNK + c1);
            }
            if ((int)cv[0].w >= 0) cold_mark(sb, tid >> 2);
            m = __reduce_or_sync(0xffffffffu, ~cv[1].w & 0x80u);
        }
        uint32_t pos[2][3];
#pragma unroll
        for (int p = 0; p < 3; p++) pos[0][p] = atoms_inc(sb + SM_NCNT + __byte_perm(cv[0].w, 0, 0x4440 + p) * 4);
        if (m) {
#pragma unroll
            for (int p = 0; p < 3; p++) pos[1][p] = atoms_inc(sb + SM_NCNT + __byte_perm(cv[1].w, 0, 0x4440 + p) * 4);
        }
        bar_sync(BAR_READY, LT);
        bool rare = false;
        if (w == WS - 1) {
            const uint32_t a = sb + SM_NCNT + min(lane, 23) * 16;
            uint4 cnt = lds128(a);
            const uint32_t fl = lds32(sb + SM_MISC + 6 * 4);
#pragma unroll 1
            while (true) {
                const uint32_t s = cnt.x + cnt.y + cnt.z + cnt.w;
                uint32_t inc = s;
#pragma unroll
                for (int o2 = 1; o2 < 32; o2 <<= 1)
                    asm volatile("{.reg .pred p; .reg .u32 t; shfl.sync.up.b32 t|p, %0, %1, 0, 0xffffffff; @p add.u32 %0, %0, t;}" : "+r"(inc) : "r"(o2));
                const uint32_t ex = inc - s;
                if (lane < 24) sts128(a + (SM_OFF - SM_NCNT), ex, ex + cnt.x, ex + cnt.x + cnt.y, ex + cnt.x + cnt.y + cnt.z);
                if (__builtin_expect(rare, 0)) {
                    if (__shfl_sync(0xffffffffu, inc, 23) > (uint32_t)CAP && lane < 23) sts128(a + (SM_OFF - SM_NCNT), 0u, 0u, 0u, 0u);
                    break;
                }
                if (__builtin_expect(!__any_sync(0xffffffffu, fl != 0u), 1)) break;
                rare = true;
                cold_count(sb, lane);
                const uint4 o = lds128(a + (SM_OCNT - SM_NCNT));
                cnt.x += o.x; cnt.y += o.y; cnt.z += o.z; cnt.w += o.w;
            }
        }
        bar_sync(BAR_READY, LT);
#pragma unroll
        for (int p = 0; p < 3; p++) pos[0][p] += lds32(sb + SM_OFF + __byte_perm(cv[0].w, 0, 0x4440 + p) * 4);
        if (m) {
#pragma unroll
            for (int p = 0; p < 3; p++) pos[1][p] += lds32(sb + SM_OFF + __byte_perm(cv[1].w, 0, 0x4440 + p) * 4);
        }
        T = (int)__shfl_sync(0xffffffffu, lds32(sb + SM_OFF + 95 * 4), 0);
        {
            const uint32_t wd[3] = {cv[0].x, cv[0].y, cv[0].z};
#pragma unroll
            for (int p = 0; p < 3; p++) {
                const uint32_t id = __byte_perm(cv[0].w, 0, 0x4440 + p);
                put_valid(sb + SM_LIST, pos[0][p], id, wd[p]);
            }
        }
        if (m) {
            const uint32_t wd[3] = {cv[1].x, cv[1].y, cv[1].z};
#pragma unroll
            for (int p = 0; p < 3; p++) {
                const uint32_t id = __byte_perm(cv[1].w, 0, 0x4440 + p);
                put_valid(sb + SM_LIST, pos[1][p], id, wd[p]);
            }
        }
        if (w == WS - 1) {
            put_entry(sb + SM_LIST, min(T, CAP) + lane, DUMMY_ID, 0u);
            if (__builtin_expect(rare && T <= CAP, 0)) cold_put(sb, lane);
        }
    }
    const int ngr = (min(T, CAP) + GR - 1) / GR;
    auto first_edge = [&](int ww) { return (int)(((uint32_t)(WA * ww + WB * max(ww - 3 * WPS, 0)) * (uint32_t)ngr) / WTOT) * GR; };
    const int rw = (w & 3) * WPS + (w >> 2);
    const int e0 = first_edge(rw), e1 = first_edge(rw + 1);
    const char* Pl = P + lane16;
    asm volatile("" : "+l"(Pl), "+r"(sH), "+r"(lsw));
    bar_sync(BAR_READY, LT);
    if (tid == 0) sts32(sb + SM_MISC + 8 * 4, 1u);

    auto part_addr = [&](int r) { return sb + SM_W1 + (r / 6) * 16384 + 10240 + (r % 6) * 1024 + lane16; };
    auto store_h = [&](uint32_t id, const float* a) {
        sts128(row_addr(id), pack_bf16(a[0], a[1]), pack_bf16(a[2], a[3]), pack_bf16(a[4], a[5]), pack_bf16(a[6], a[7]));
    };
    {
        const uint32_t sL = sb + SM_LIST;
        uint32_t cur = 0, mask = 0;
        bool lead = false, chk = true;
        uint32_t qp[4], v[4], wp[4] = {0u, 0u, 0u, 0u}, yA[U], yB[U];
        uint4 bufA[U], bufB[U];
        float acc[8], u0 = 0.f, u1 = 0.f;
        uint32_t xa = sL + e0 * 8;
        auto load_q = [&](uint32_t id) { const uint4 t = lds128(row_addr(id)); qp[0] = t.x; qp[1] = t.y; qp[2] = t.z; qp[3] = t.w; };
        auto issue = [&](uint32_t a, uint4* buf, uint32_t* y) {
#pragma unroll
            for (int k = 0; k < U; k += 2) {
                const uint4 t = lds128(a + k * 8);
                buf[k] = ldg128_l2(Pl + (size_t)t.x * 512);
                buf[k + 1] = ldg128_l2(Pl + (size_t)t.z * 512);
                y[k] = t.y; y[k + 1] = t.w;
            }
        };
        auto verify = [&](uint32_t a, uint4* buf, uint32_t* y) {
#pragma unroll 1
            for (int it = 0;; it++) {
                uint32_t bad = 0;
#pragma unroll
                for (int k = 0; k < U; k++) bad |= buf[k].x ^ ptag;
                if (!__any_sync(0xffffffffu, (bad & 1u) && it < (1 << 22))) break;
                issue(a, buf, y);
            }
            uint32_t f;
            asm volatile("ld.acquire.cta.shared.u32 %0, [%1];" : "=r"(f) : "r"(sb + SM_MISC + 7 * 4) : "memory");
            chk = __any_sync(0xffffffffu, f == 0u);
        };
        auto refill = [&](int eb) {
            const int i = eb + lane;
            mask = __ballot_sync(0xffffffffu, (i + 1 < e1) && (lds8(sL + i * 8 + 4) != lds8(sL + i * 8 + 12)));
        };
        auto zpart = [&](uint32_t y, const uint4& p, uint32_t* o) {
            o[0] = add_half(hfma2_hi(y, wp[0], qp[0]), p.x); o[1] = add_half(hfma2_hi(y, wp[1], qp[1]), p.y);
            o[2] = add_half(hfma2_hi(y, wp[2], qp[2]), p.z); o[3] = add_half(hfma2_hi(y, wp[3], qp[3]), p.w);
        };
        auto act = [&]() {
            float u[8];
            u[0] = u0; u[1] = u1;
#pragma unroll
            for (int j = 1; j < 4; j++) { u[2 * j] = j < 3 ? bf_lo_alu(v[j]) : bf_lo(v[j]); u[2 * j + 1] = bf_hi(v[j]); }
#pragma unroll
            for (int j = 0; j < 8; j++) acc[j] += fmaf(u[j], tanh_fast(u[j]), u[j]);
        };
        auto publish = [&]() {
            const uint32_t pa = part_addr(rw);
            sts128(pa, __float_as_uint(acc[0]), __float_as_uint(acc[1]), __float_as_uint(acc[2]), __float_as_uint(acc[3]));
            sts128(pa + 512, __float_as_uint(acc[4]), __float_as_uint(acc[5]), __float_as_uint(acc[6]), __float_as_uint(acc[7]));
            asm volatile("mbarrier.arrive.release.cta.shared::cta.b64 _, [%0];" :: "r"(mb + (MB_PART + rw) * 8) : "memory");
        };
        auto slot = [&](int k, uint32_t yn, const uint4& pn) {
            uint32_t vn[4];
            if (mask & (1u << k)) {
                const uint32_t nid = yn & 0xffu;
                load_q(nid);
                act();
                if (lead) { publish(); lead = false; } else store_h(cur, acc);
#pragma unroll
                for (int j = 0; j < 8; j++) acc[j] = 0.f;
                cur = nid;
                zpart(yn, pn, vn);
            } else {
                zpart(yn, pn, vn);
                act();
            }
#pragma unroll
            for (int j = 0; j < 4; j++) v[j] = vn[j];
            u0 = bf_lo_alu(v[0]); u1 = bf_hi(v[0]);
        };
        if (T <= CAP) issue(xa, bufA, yA);
        if (__builtin_expect(T > CAP, 0)) cold_direct(sb, cells, P);
        else if (e0 < e1) {
            const uint4 wc_raw = lds128(sb + SM_CONST + lane16);
            wp[0] = hmul2(wc_raw.x, HALF2); wp[1] = hmul2(wc_raw.y, HALF2); wp[2] = hmul2(wc_raw.z, HALF2); wp[3] = hmul2(wc_raw.w, HALF2);
            cur = yA[0] & 0xffu;
            lead = __any_sync(0xffffffffu, (e0 > 0) && (lds8(xa - 4) == cur));
            load_q(cur);
            refill(e0);
#pragma unroll
            for (int j = 0; j < 8; j++) acc[j] = 0.f;
            verify(xa, bufA, yA);
            issue(xa + 16, bufB, yB);
            zpart(yA[0], bufA[0], v);
            u0 = bf_lo_alu(v[0]); u1 = bf_hi(v[0]);
            int e = e0;
            auto trip = [&](bool checked) {
                slot(0, yA[1], bufA[1]);
                if (checked && e + 2 < e1) verify(xa + 16, bufB, yB);
                slot(1, yB[0], bufB[0]);
                if (e + 2 >= e1) return false;
                if (e + 4 < e1) issue(xa + 32, bufA, yA);
                slot(2, yB[1], bufB[1]);
                if (checked && e + 4 < e1) verify(xa + 32, bufA, yA);
                slot(3, yA[0], bufA[0]);
                mask >>= 4; e += 4; xa += 32;
                if (e >= e1) return false;
                if (e + 2 < e1) issue(xa + 16, bufB, yB);
                if (((e - e0) & 31) == 0) refill(e);
                return true;
            };
            bool more = true;
#pragma unroll 1
            while (more) more = trip(chk);
            if (e1 < T && lds8(sL + e1 * 8 + 4) == cur) {
                int wn = rw + 1;
#pragma unroll 1
                while (first_edge(wn + 1) == e1) wn++;
                mbar_wait(mb + (MB_PART + wn) * 8);
                const uint4 a = lds128(part_addr(wn)), b = lds128(part_addr(wn) + 512);
                acc[0] += __uint_as_float(a.x); acc[1] += __uint_as_float(a.y); acc[2] += __uint_as_float(a.z); acc[3] += __uint_as_float(a.w);
                acc[4] += __uint_as_float(b.x); acc[5] += __uint_as_float(b.y); acc[6] += __uint_as_float(b.z); acc[7] += __uint_as_float(b.w);
            }
            if (lead) publish(); else store_h(cur, acc);
        }
    }
    fence_async();
    }
    }
    if (PHASE == 1) return;
    const uint32_t fa = desc_lo(sb + SM_W0 + (wg & 1) * 32768), fb = desc_lo(sb + SM_W1);
    __syncthreads();
    if (w < 8) {
        mbar_wait(mb + MB_W2 * 8);
        gemm80<16, 16384, 0>(d, fa, fb);
        const uint32_t ba = sb + SM_CONST + 1024 + (w * 16 + (lane >> 2)) * 2;
        const float c_lo = bf_lo(lds16(ba)), c_hi = bf_lo(lds16(ba + 16));
        uint2 dg[10];
#pragma unroll
        for (int i = 0; i < 10; i++) dg[i] = lds64(sb + SM_DEG + (8 * i + 2 * (lane & 3)) * 4);
        const uint32_t stg = sb + SM_X + wg * 10240, frag_off = frag_offset(lane, wq);
        wg_wait(d);
#pragma unroll
        for (int i = 0; i < 5; i++) {
            const float d0 = __uint_as_float(dg[2 * i].x), d1 = __uint_as_float(dg[2 * i].y), d2 = __uint_as_float(dg[2 * i + 1].x), d3 = __uint_as_float(dg[2 * i + 1].y);
            stsm4t(stg + i * 2048 + frag_off,
                   pack_bf16(fmaf(d0, c_lo, d[8 * i + 0]), fmaf(d1, c_lo, d[8 * i + 1])), pack_bf16(fmaf(d0, c_hi, d[8 * i + 2]), fmaf(d1, c_hi, d[8 * i + 3])),
                   pack_bf16(fmaf(d2, c_lo, d[8 * i + 4]), fmaf(d3, c_lo, d[8 * i + 5])), pack_bf16(fmaf(d2, c_hi, d[8 * i + 6]), fmaf(d3, c_hi, d[8 * i + 7])));
        }
        fence_async();
        bar_sync(BAR_WG0 + wg, 128);
        if (wq == 0 && elect_one()) {
            tma_store(&tm_out, node0, wg, stg);
            asm volatile("cp.async.bulk.commit_group;" ::: "memory");
            asm volatile("cp.async.bulk.wait_group.read 0;" ::: "memory");
        }
    }
}

}

typedef CUresult (*EncodeTiledFn)(CUtensorMap*, CUtensorMapDataType, cuuint32_t, void*, const cuuint64_t*, const cuuint64_t*,
                                  const cuuint32_t*, const cuuint32_t*, CUtensorMapInterleave, CUtensorMapSwizzle,
                                  CUtensorMapL2promotion, CUtensorMapFloatOOBfill);

static void make_map(EncodeTiledFn enc, CUtensorMap* m, const void* base, int cols, int rows, int box_rows, int box_blocks) {
    cuuint64_t dims[3] = {64, (cuuint64_t)rows, (cuuint64_t)(cols / 64)};
    cuuint64_t strides[2] = {(cuuint64_t)cols * 2, 128};
    cuuint32_t box[3] = {64, (cuuint32_t)box_rows, (cuuint32_t)box_blocks};
    cuuint32_t estr[3] = {1, 1, 1};
    enc(m, CU_TENSOR_MAP_DATA_TYPE_BFLOAT16, 3, const_cast<void*>(base), dims, strides, box, estr, CU_TENSOR_MAP_INTERLEAVE_NONE,
        CU_TENSOR_MAP_SWIZZLE_128B, CU_TENSOR_MAP_L2_PROMOTION_L2_128B, CU_TENSOR_MAP_FLOAT_OOB_FILL_NONE);
}

extern "C" void kernel_launch(void* const* d_in, const int* in_sizes, int n_in, void* d_out, int out_size) {
    (void)in_sizes; (void)n_in; (void)out_size;
    static int fused = -1;
    static EncodeTiledFn enc = nullptr;
    static void *p_addr = nullptr, *c_addr = nullptr, *bar_addr = nullptr;
    if (fused < 0) {
        cudaFuncSetAttribute(mpnn_kernel<0>, cudaFuncAttributeMaxDynamicSharedMemorySize, SMEM_BYTES);
        cudaFuncSetAttribute(mpnn_kernel<1>, cudaFuncAttributeMaxDynamicSharedMemorySize, SMEM_BYTES);
        cudaFuncSetAttribute(mpnn_kernel<2>, cudaFuncAttributeMaxDynamicSharedMemorySize, SMEM_BYTES);
        int dev = 0, sms = 0, occ = 0;
        cudaGetDevice(&dev);
        cudaDeviceGetAttribute(&sms, cudaDevAttrMultiProcessorCount, dev);
        cudaOccupancyMaxActiveBlocksPerMultiprocessor(&occ, mpnn_kernel<0>, NT, SMEM_BYTES);
        void* fn = nullptr;
        cudaDriverEntryPointQueryResult qr;
        cudaGetDriverEntryPoint("cuTensorMapEncodeTiled", &fn, cudaEnableDefault, &qr);
        enc = (EncodeTiledFn)fn;
        cudaGetSymbolAddress(&p_addr, g_P);
        cudaGetSymbolAddress(&c_addr, g_cells);
        cudaGetSymbolAddress(&bar_addr, g_bar);
        fused = (sms * occ >= G) ? 1 : 0;
    }
    CUtensorMap tx, tw1, tp, tw2, tout;
    make_map(enc, &tx, d_in[0], 128, N_NODES, 80, 2);
    make_map(enc, &tw1, d_in[4], 256, 257, 128, 4);
    make_map(enc, &tp, p_addr, 256, N_NODES, NB, 1);
    make_map(enc, &tw2, d_in[6], 128, 256, 256, 2);
    make_map(enc, &tout, d_out, 128, N_NODES, NB, 1);
    cudaStream_t st = cudaStreamPerThread;
#define MPNN_ARGS (const int2*)d_in[3], (const int2*)d_in[2], (const uint32_t*)d_in[1], (uint4*)c_addr, \
    (const char*)p_addr, (GridBar*)bar_addr, (const char*)d_in[4], (const char*)d_in[5], (const char*)d_in[7], tx, tw1, tp, tw2, tout
    if (fused) {
        mpnn_kernel<0><<<G, NT, SMEM_BYTES, st>>>(MPNN_ARGS);
    } else {
        mpnn_kernel<1><<<G, NT, SMEM_BYTES, st>>>(MPNN_ARGS);
        mpnn_kernel<2><<<G, NT, SMEM_BYTES, st>>>(MPNN_ARGS);
    }
}
```
